```python
import torch

def _softmax(x, axis=-1):
    return torch.softmax(x, dim=axis)
def _gelu(x):
    return torch.nn.functional.gelu(x, approximate="tanh")
def _silu(x):
    return torch.nn.functional.silu(x)
def _sigmoid(x):
    return torch.sigmoid(x)
def _layernorm(x, axis=-1, eps=1e-5):
    m = x.mean(dim=axis, keepdim=True)
    v = x.var(dim=axis, keepdim=True, unbiased=False)
    return (x - m) / torch.sqrt(v + eps)
def _scatter_add(tgt, idx, src, axis=0):
    return tgt.clone().index_add_(axis, idx, src)
def _segment_sum(src, seg, n):
    out = torch.zeros((n,) + src.shape[1:], dtype=src.dtype)
    return out.index_add_(0, seg, src)
def _pad(x, pw):
    flat = tuple(v for pair in reversed(pw) for v in pair)
    return torch.nn.functional.pad(x, flat)

kernel_name = 'concat_heads__sliding_local_dilated__sliding_local_dilated__prompt'

def setup_inputs():

    _w = (lambda a: (lambda t: t.to(torch.bfloat16) if t.is_floating_point() else t)(torch.as_tensor(a)))
    def _A_setup():
        B, S, D = 1, 2048, 1024
        return {
            "x": _w((lambda *s: torch.randn(*s, dtype=torch.bfloat16) * 0.2)(B, S, D)),
            "wqkv": _w((lambda *s: torch.randn(*s, dtype=torch.bfloat16) * 0.2)(D, 3 * D)),
            "wo": _w((lambda *s: torch.randn(*s, dtype=torch.bfloat16) * 0.05)(D, D)),
        }
    _A_in = _A_setup()

    def _B_setup():
        B, S, D = 1, 2048, 1024
        return {
            "x": _w((lambda *s: torch.randn(*s, dtype=torch.bfloat16) * 0.2)(B, S, D)),
            "wqkv": _w((lambda *s: torch.randn(*s, dtype=torch.bfloat16) * 0.2)(D, 3 * D)),
            "wo": _w((lambda *s: torch.randn(*s, dtype=torch.bfloat16) * 0.05)(D, D)),
        }
    _B_in = _B_setup()

    return {
        "A_x": _A_in["x"],
        "A_wqkv": _A_in["wqkv"],
        "A_wo": _A_in["wo"],
        "B_x": _B_in["x"],
        "B_wqkv": _B_in["wqkv"],
        "B_wo": _B_in["wo"],
    }

def reference(A_x, A_wqkv, A_wo, B_x, B_wqkv, B_wo):
    def _A_ref(x, wqkv, wo):
        B, S, D = x.shape
        H = 32; Dh = D // H
        W, dil = 8, 2
        qkv = (lambda x, *d: x.permute(*d))((x @ wqkv).reshape(B, S, 3, H, Dh), 2, 0, 3, 1, 4)
        q, k, v = qkv[0], qkv[1], qkv[2]
        scale = Dh ** -0.5
        pos = torch.arange(S)
        off = torch.arange(W) * dil
        idx = pos[:, None] - off[None, :]
        mask = idx >= 0
        idx_c = torch.where(mask, idx, 0).reshape(-1)
        kg = k[:, :, idx_c, :].reshape(B, H, S, W, Dh)
        vg = v[:, :, idx_c, :].reshape(B, H, S, W, Dh)
        logits = torch.einsum("bhsd,bhswd->bhsw", q, kg) * scale
        logits = torch.where(mask[None, None, :, :], logits, -1e9)
        attn = _softmax(logits, axis=-1)
        o = torch.einsum("bhsw,bhswd->bhsd", attn, vg)
        return (lambda x, *d: x.permute(*d))(o, 0, 2, 1, 3).reshape(B, S, D) @ wo

    def _B_ref(x, wqkv, wo):
        B, S, D = x.shape
        H = 32; Dh = D // H
        W, dil = 8, 2
        qkv = (lambda x, *d: x.permute(*d))((x @ wqkv).reshape(B, S, 3, H, Dh), 2, 0, 3, 1, 4)
        q, k, v = qkv[0], qkv[1], qkv[2]
        scale = Dh ** -0.5
        pos = torch.arange(S)
        off = torch.arange(W) * dil
        idx = pos[:, None] - off[None, :]
        mask = idx >= 0
        idx_c = torch.where(mask, idx, 0).reshape(-1)
        kg = k[:, :, idx_c, :].reshape(B, H, S, W, Dh)
        vg = v[:, :, idx_c, :].reshape(B, H, S, W, Dh)
        logits = torch.einsum("bhsd,bhswd->bhsw", q, kg) * scale
        logits = torch.where(mask[None, None, :, :], logits, -1e9)
        attn = _softmax(logits, axis=-1)
        o = torch.einsum("bhsw,bhswd->bhsd", attn, vg)
        return (lambda x, *d: x.permute(*d))(o, 0, 2, 1, 3).reshape(B, S, D) @ wo

    a = _A_ref(A_x, A_wqkv, A_wo)
    b = _B_ref(B_x, B_wqkv, B_wo)
    return torch.concatenate([a, b], axis=-1)
```

```cpp
#include <cuda_runtime.h>
#include <cuda_bf16.h>
#include <cuda.h>
#include <stdint.h>
#include <type_traits>

namespace {

__device__ __forceinline__ void wgmma_n192(float (&d)[128], uint64_t da, uint64_t db, int scale_d) {
  asm volatile("{\n.reg .pred p;\nsetp.ne.b32 p, %98, 0;\n"
    "wgmma.mma_async.sync.aligned.m64n192k16.f32.bf16.bf16 "
    "{%0, %1, %2, %3, %4, %5, %6, %7, %8, %9, %10, %11, %12, %13, %14, %15, "
    "%16, %17, %18, %19, %20, %21, %22, %23, %24, %25, %26, %27, %28, %29, %30, %31, "
    "%32, %33, %34, %35, %36, %37, %38, %39, %40, %41, %42, %43, %44, %45, %46, %47, "
    "%48, %49, %50, %51, %52, %53, %54, %55, %56, %57, %58, %59, %60, %61, %62, %63, "
    "%64, %65, %66, %67, %68, %69, %70, %71, %72, %73, %74, %75, %76, %77, %78, %79, "
    "%80, %81, %82, %83, %84, %85, %86, %87, %88, %89, %90, %91, %92, %93, %94, %95}, "
    "%96, %97, p, 1, 1, 0, 1;\n}\n"
    : "+f"(d[0]), "+f"(d[1]), "+f"(d[2]), "+f"(d[3]), "+f"(d[4]), "+f"(d[5]), "+f"(d[6]), "+f"(d[7]),
      "+f"(d[8]), "+f"(d[9]), "+f"(d[10]), "+f"(d[11]), "+f"(d[12]), "+f"(d[13]), "+f"(d[14]), "+f"(d[15]),
      "+f"(d[16]), "+f"(d[17]), "+f"(d[18]), "+f"(d[19]), "+f"(d[20]), "+f"(d[21]), "+f"(d[22]), "+f"(d[23]),
      "+f"(d[24]), "+f"(d[25]), "+f"(d[26]), "+f"(d[27]), "+f"(d[28]), "+f"(d[29]), "+f"(d[30]), "+f"(d[31]),
      "+f"(d[32]), "+f"(d[33]), "+f"(d[34]), "+f"(d[35]), "+f"(d[36]), "+f"(d[37]), "+f"(d[38]), "+f"(d[39]),
      "+f"(d[40]), "+f"(d[41]), "+f"(d[42]), "+f"(d[43]), "+f"(d[44]), "+f"(d[45]), "+f"(d[46]), "+f"(d[47]),
      "+f"(d[48]), "+f"(d[49]), "+f"(d[50]), "+f"(d[51]), "+f"(d[52]), "+f"(d[53]), "+f"(d[54]), "+f"(d[55]),
      "+f"(d[56]), "+f"(d[57]), "+f"(d[58]), "+f"(d[59]), "+f"(d[60]), "+f"(d[61]), "+f"(d[62]), "+f"(d[63]),
      "+f"(d[64]), "+f"(d[65]), "+f"(d[66]), "+f"(d[67]), "+f"(d[68]), "+f"(d[69]), "+f"(d[70]), "+f"(d[71]),
      "+f"(d[72]), "+f"(d[73]), "+f"(d[74]), "+f"(d[75]), "+f"(d[76]), "+f"(d[77]), "+f"(d[78]), "+f"(d[79]),
      "+f"(d[80]), "+f"(d[81]), "+f"(d[82]), "+f"(d[83]), "+f"(d[84]), "+f"(d[85]), "+f"(d[86]), "+f"(d[87]),
      "+f"(d[88]), "+f"(d[89]), "+f"(d[90]), "+f"(d[91]), "+f"(d[92]), "+f"(d[93]), "+f"(d[94]), "+f"(d[95])
    : "l"(da), "l"(db), "r"(scale_d));
}

__device__ __forceinline__ void wgmma_n256(float (&d)[128], uint64_t da, uint64_t db, int scale_d) {
  asm volatile("{\n.reg .pred p;\nsetp.ne.b32 p, %130, 0;\n"
    "wgmma.mma_async.sync.aligned.m64n256k16.f32.bf16.bf16 "
    "{%0, %1, %2, %3, %4, %5, %6, %7, %8, %9, %10, %11, %12, %13, %14, %15, "
    "%16, %17, %18, %19, %20, %21, %22, %23, %24, %25, %26, %27, %28, %29, %30, %31, "
    "%32, %33, %34, %35, %36, %37, %38, %39, %40, %41, %42, %43, %44, %45, %46, %47, "
    "%48, %49, %50, %51, %52, %53, %54, %55, %56, %57, %58, %59, %60, %61, %62, %63, "
    "%64, %65, %66, %67, %68, %69, %70, %71, %72, %73, %74, %75, %76, %77, %78, %79, "
    "%80, %81, %82, %83, %84, %85, %86, %87, %88, %89, %90, %91, %92, %93, %94, %95, "
    "%96, %97, %98, %99, %100, %101, %102, %103, %104, %105, %106, %107, %108, %109, %110, %111, "
    "%112, %113, %114, %115, %116, %117, %118, %119, %120, %121, %122, %123, %124, %125, %126, %127}, "
    "%128, %129, p, 1, 1, 0, 1;\n}\n"
    : "+f"(d[0]), "+f"(d[1]), "+f"(d[2]), "+f"(d[3]), "+f"(d[4]), "+f"(d[5]), "+f"(d[6]), "+f"(d[7]),
      "+f"(d[8]), "+f"(d[9]), "+f"(d[10]), "+f"(d[11]), "+f"(d[12]), "+f"(d[13]), "+f"(d[14]), "+f"(d[15]),
      "+f"(d[16]), "+f"(d[17]), "+f"(d[18]), "+f"(d[19]), "+f"(d[20]), "+f"(d[21]), "+f"(d[22]), "+f"(d[23]),
      "+f"(d[24]), "+f"(d[25]), "+f"(d[26]), "+f"(d[27]), "+f"(d[28]), "+f"(d[29]), "+f"(d[30]), "+f"(d[31]),
      "+f"(d[32]), "+f"(d[33]), "+f"(d[34]), "+f"(d[35]), "+f"(d[36]), "+f"(d[37]), "+f"(d[38]), "+f"(d[39]),
      "+f"(d[40]), "+f"(d[41]), "+f"(d[42]), "+f"(d[43]), "+f"(d[44]), "+f"(d[45]), "+f"(d[46]), "+f"(d[47]),
      "+f"(d[48]), "+f"(d[49]), "+f"(d[50]), "+f"(d[51]), "+f"(d[52]), "+f"(d[53]), "+f"(d[54]), "+f"(d[55]),
      "+f"(d[56]), "+f"(d[57]), "+f"(d[58]), "+f"(d[59]), "+f"(d[60]), "+f"(d[61]), "+f"(d[62]), "+f"(d[63]),
      "+f"(d[64]), "+f"(d[65]), "+f"(d[66]), "+f"(d[67]), "+f"(d[68]), "+f"(d[69]), "+f"(d[70]), "+f"(d[71]),
      "+f"(d[72]), "+f"(d[73]), "+f"(d[74]), "+f"(d[75]), "+f"(d[76]), "+f"(d[77]), "+f"(d[78]), "+f"(d[79]),
      "+f"(d[80]), "+f"(d[81]), "+f"(d[82]), "+f"(d[83]), "+f"(d[84]), "+f"(d[85]), "+f"(d[86]), "+f"(d[87]),
      "+f"(d[88]), "+f"(d[89]), "+f"(d[90]), "+f"(d[91]), "+f"(d[92]), "+f"(d[93]), "+f"(d[94]), "+f"(d[95]),
      "+f"(d[96]), "+f"(d[97]), "+f"(d[98]), "+f"(d[99]), "+f"(d[100]), "+f"(d[101]), "+f"(d[102]), "+f"(d[103]),
      "+f"(d[104]), "+f"(d[105]), "+f"(d[106]), "+f"(d[107]), "+f"(d[108]), "+f"(d[109]), "+f"(d[110]), "+f"(d[111]),
      "+f"(d[112]), "+f"(d[113]), "+f"(d[114]), "+f"(d[115]), "+f"(d[116]), "+f"(d[117]), "+f"(d[118]), "+f"(d[119]),
      "+f"(d[120]), "+f"(d[121]), "+f"(d[122]), "+f"(d[123]), "+f"(d[124]), "+f"(d[125]), "+f"(d[126]), "+f"(d[127])
    : "l"(da), "l"(db), "r"(scale_d));
}

#define MAP 2
#define ORDER 1
constexpr int NUM_CTAS = 128;
constexpr int NUM_THREADS = 384;
constexpr int G1_STAGES = 5, G2_STAGES = 4;
constexpr uint32_t A_BYTES = 16384;
constexpr uint32_t G1_STAGE = 40960;
constexpr uint32_t G2_STAGE = 49152;
constexpr uint32_t RING_BYTES = G1_STAGES * G1_STAGE;
constexpr uint32_t OFF_X = RING_BYTES;
constexpr uint32_t OFF_BAR = OFF_X + 9 * 2048;
constexpr uint32_t SMEM_BYTES = OFF_BAR + 512;
constexpr uint32_t SPIN_LIMIT = 1u << 24;

struct alignas(64) TMaps {
  CUtensorMap x[2], w[2], wo[2], o, out;
};

__device__ __nv_bfloat16 g_o[4 * 1024 * 1024];
__device__ ulonglong2 g_halo[NUM_CTAS * 4 * 256];
__device__ unsigned g_o_ready[32 * 4];
__device__ unsigned g_epoch[NUM_CTAS];
#define TS(slot)
#define KS(i)

__device__ __forceinline__ void mbar_init(uint32_t bar, uint32_t count) {
  asm volatile("mbarrier.init.shared::cta.b64 [%0], %1;" ::"r"(bar), "r"(count) : "memory");
}
__device__ __forceinline__ bool mbar_try_wait(uint32_t bar, uint32_t parity) {
  uint32_t ok;
  asm volatile("{\n.reg .pred p;\nmbarrier.try_wait.parity.shared::cta.b64 p, [%1], %2;\nselp.u32 %0, 1, 0, p;\n}\n"
               : "=r"(ok) : "r"(bar), "r"(parity) : "memory");
  return ok != 0;
}
__device__ __forceinline__ void mbar_wait(uint32_t bar, uint32_t parity) {
  uint32_t spins = 0;
  while (!mbar_try_wait(bar, parity)) { if (++spins > SPIN_LIMIT) __trap(); }
}
__device__ __forceinline__ void mbar_arrive(uint32_t bar) {
  asm volatile("mbarrier.arrive.shared::cta.b64 _, [%0];" ::"r"(bar) : "memory");
}
__device__ __forceinline__ void mbar_arrive_cluster(uint32_t bar_cluster_addr) {
  asm volatile("mbarrier.arrive.shared::cluster.b64 _, [%0];" ::"r"(bar_cluster_addr) : "memory");
}
__device__ __forceinline__ void mbar_expect_tx(uint32_t bar, uint32_t bytes) {
  asm volatile("mbarrier.arrive.expect_tx.shared::cta.b64 _, [%0], %1;" ::"r"(bar), "r"(bytes) : "memory");
}
__device__ __forceinline__ uint32_t mapa(uint32_t addr, uint32_t rank) {
  uint32_t r; asm("mapa.shared::cluster.u32 %0, %1, %2;" : "=r"(r) : "r"(addr), "r"(rank)); return r;
}
__device__ __forceinline__ void tma_load_2d(uint32_t dst, const CUtensorMap* m, int c0, int c1, uint32_t bar) {
  asm volatile("cp.async.bulk.tensor.2d.shared::cluster.global.mbarrier::complete_tx::bytes [%0], [%1, {%3, %4}], [%2];"
               ::"r"(dst), "l"(m), "r"(bar), "r"(c0), "r"(c1) : "memory");
}
__device__ __forceinline__ void tma_load_3d_mc(uint32_t dst, const CUtensorMap* m, int c0, int c1, int c2, uint32_t bar, uint16_t mask) {
  asm volatile("cp.async.bulk.tensor.3d.shared::cluster.global.mbarrier::complete_tx::bytes.multicast::cluster [%0], [%1, {%3, %4, %5}], [%2], %6;"
               ::"r"(dst), "l"(m), "r"(bar), "r"(c0), "r"(c1), "r"(c2), "h"(mask) : "memory");
}
__device__ __forceinline__ void tma_store_2d(const CUtensorMap* m, int c0, int c1, uint32_t src) {
  asm volatile("cp.async.bulk.tensor.2d.global.shared::cta.bulk_group [%0, {%2, %3}], [%1];"
               ::"l"(m), "r"(src), "r"(c0), "r"(c1) : "memory");
}
__device__ __forceinline__ void bulk_commit() { asm volatile("cp.async.bulk.commit_group;" ::: "memory"); }
__device__ __forceinline__ void bulk_wait0() { asm volatile("cp.async.bulk.wait_group 0;" ::: "memory"); }
__device__ __forceinline__ void bulk_wait0_read() { asm volatile("cp.async.bulk.wait_group.read 0;" ::: "memory"); }
__device__ __forceinline__ void fence_async_smem() { asm volatile("fence.proxy.async.shared::cta;" ::: "memory"); }
__device__ __forceinline__ void prefetch_tmap(const CUtensorMap* m) {
  asm volatile("prefetch.tensormap [%0];" ::"l"(m) : "memory");
}
__device__ __forceinline__ void wgmma_fence() { asm volatile("wgmma.fence.sync.aligned;" ::: "memory"); }
__device__ __forceinline__ void wgmma_commit() { asm volatile("wgmma.commit_group.sync.aligned;" ::: "memory"); }
template <int N> __device__ __forceinline__ void wgmma_wait() { asm volatile("wgmma.wait_group.sync.aligned %0;" ::"n"(N) : "memory"); }
template <int N> __device__ __forceinline__ void fence_acc(float (&d)[128]) {
#pragma unroll
  for (int i = 0; i < N; i++) asm volatile("" : "+f"(d[i])::"memory");
}
__device__ __forceinline__ void bar_sync(int id) { asm volatile("bar.sync %0, 256;" ::"r"(id) : "memory"); }
__device__ __forceinline__ void bar_arrive(int id) { asm volatile("bar.arrive %0, 256;" ::"r"(id) : "memory"); }
__device__ __forceinline__ uint64_t desc_kmajor(uint32_t addr) {
  return (uint64_t)((addr & 0x3FFFF) >> 4) | (1ull << 16) | (64ull << 32) | (1ull << 62);
}
__device__ __forceinline__ uint64_t desc_mnmajor(uint32_t addr) {
  return (uint64_t)((addr & 0x3FFFF) >> 4) | (256ull << 16) | (64ull << 32) | (1ull << 62);
}
__device__ __forceinline__ uint32_t pack_bf16(float lo, float hi) {
  uint32_t r; asm("cvt.rn.bf16x2.f32 %0, %1, %2;" : "=r"(r) : "f"(hi), "f"(lo)); return r;
}
__device__ __forceinline__ void stsm_x4(uint32_t addr, uint32_t r0, uint32_t r1, uint32_t r2, uint32_t r3) {
  asm volatile("stmatrix.sync.aligned.m8n8.x4.shared.b16 [%0], {%1, %2, %3, %4};" ::"r"(addr), "r"(r0), "r"(r1), "r"(r2), "r"(r3) : "memory");
}
__device__ __forceinline__ void stsm_x4_t(uint32_t addr, uint32_t r0, uint32_t r1, uint32_t r2, uint32_t r3) {
  asm volatile("stmatrix.sync.aligned.m8n8.x4.trans.shared.b16 [%0], {%1, %2, %3, %4};" ::"r"(addr), "r"(r0), "r"(r1), "r"(r2), "r"(r3) : "memory");
}
__device__ __forceinline__ uint32_t movm_t(uint32_t a) {
  uint32_t d; asm volatile("movmatrix.sync.aligned.m8n8.trans.b16 %0, %1;" : "=r"(d) : "r"(a)); return d;
}
__device__ __forceinline__ void mma_init(float (&c)[4], uint32_t a0, uint32_t a1, uint32_t a2, uint32_t a3, uint32_t b0, uint32_t b1) {
  asm volatile("mma.sync.aligned.m16n8k16.row.col.f32.bf16.bf16.f32 {%0, %1, %2, %3}, {%4, %5, %6, %7}, {%8, %9}, {%10, %10, %10, %10};"
               : "=f"(c[0]), "=f"(c[1]), "=f"(c[2]), "=f"(c[3]) : "r"(a0), "r"(a1), "r"(a2), "r"(a3), "r"(b0), "r"(b1), "f"(0.f));
}
__device__ __forceinline__ void mma_acc(float (&c)[4], uint32_t a0, uint32_t a1, uint32_t a2, uint32_t a3, uint32_t b0, uint32_t b1) {
  asm volatile("mma.sync.aligned.m16n8k16.row.col.f32.bf16.bf16.f32 {%0, %1, %2, %3}, {%4, %5, %6, %7}, {%8, %9}, {%0, %1, %2, %3};"
               : "+f"(c[0]), "+f"(c[1]), "+f"(c[2]), "+f"(c[3]) : "r"(a0), "r"(a1), "r"(a2), "r"(a3), "r"(b0), "r"(b1));
}
__device__ __forceinline__ float ex2(float x) { float y; asm("ex2.approx.ftz.f32 %0, %1;" : "=f"(y) : "f"(x)); return y; }
__device__ __forceinline__ unsigned ld_acquire(const unsigned* p) {
  unsigned v; asm volatile("ld.acquire.gpu.global.u32 %0, [%1];" : "=r"(v) : "l"(p) : "memory"); return v;
}
__device__ __forceinline__ void wait_flag(const unsigned* p, unsigned target) {
  uint32_t spins = 0;
  while ((int)(ld_acquire(p) - target) < 0) { if (++spins > SPIN_LIMIT) __trap(); __nanosleep(20); }
}
__device__ __forceinline__ uint4 lds128(uint32_t addr) {
  uint4 v; asm volatile("ld.shared.v4.u32 {%0, %1, %2, %3}, [%4];" : "=r"(v.x), "=r"(v.y), "=r"(v.z), "=r"(v.w) : "r"(addr) : "memory"); return v;
}
__device__ __forceinline__ void sts128(uint32_t addr, uint32_t a, uint32_t b, uint32_t c, uint32_t d) {
  asm volatile("st.shared.v4.u32 [%0], {%1, %2, %3, %4};" ::"r"(addr), "r"(a), "r"(b), "r"(c), "r"(d) : "memory");
}

template <int N>
__device__ __forceinline__ void softmax_exp(const float (&lo)[N][2], const float (&hi)[N][2], bool use_lo0, bool use_lo1,
                                            float (&ex)[N][2]) {
  constexpr float kScale = 0.17677669529663687f * 1.4426950408889634f;
  float m[N];
#pragma unroll
  for (int i = 0; i < N; i++) { ex[i][0] = use_lo0 ? lo[i][0] : hi[i][0]; ex[i][1] = use_lo1 ? lo[i][1] : hi[i][1]; m[i] = fmaxf(ex[i][0], ex[i][1]); }
#pragma unroll
  for (int i = 0; i < N; i++) m[i] = fmaxf(m[i], __shfl_xor_sync(0xffffffffu, m[i], 1));
#pragma unroll
  for (int i = 0; i < N; i++) m[i] = fmaxf(m[i], __shfl_xor_sync(0xffffffffu, m[i], 2));
#pragma unroll
  for (int i = 0; i < N; i++) { ex[i][0] = ex2((ex[i][0] - m[i]) * kScale); ex[i][1] = ex2((ex[i][1] - m[i]) * kScale); }
}
template <int N>
__device__ __forceinline__ void softmax_norm(const float (&ex)[N][2], uint32_t lo_mask, uint32_t (&b_lo)[N], uint32_t (&b_hi)[N]) {
  float s[N];
#pragma unroll
  for (int i = 0; i < N; i++) s[i] = ex[i][0] + ex[i][1];
#pragma unroll
  for (int i = 0; i < N; i++) s[i] += __shfl_xor_sync(0xffffffffu, s[i], 1);
#pragma unroll
  for (int i = 0; i < N; i++) s[i] += __shfl_xor_sync(0xffffffffu, s[i], 2);
#pragma unroll
  for (int i = 0; i < N; i++) {
    const float r = __fdividef(1.0f, s[i]);
    const uint32_t p = pack_bf16(ex[i][0] * r, ex[i][1] * r);
    b_lo[i] = p & lo_mask;
    b_hi[i] = p & ~lo_mask;
  }
}

__global__ void __cluster_dims__(2, 1, 1) __launch_bounds__(NUM_THREADS, 1)
fused_kernel(const __grid_constant__ TMaps tm) {
  extern __shared__ __align__(1024) uint8_t smem_raw[];
  const uint32_t sb = (uint32_t)__cvta_generic_to_shared(smem_raw);
  const int warp = __shfl_sync(0xffffffffu, threadIdx.x >> 5, 0), lane = threadIdx.x & 31;
  const int e = blockIdx.x & 1;
  int cg, rb, br;
  {
    const int c = blockIdx.x >> 1;
    int q, i;
    if (c < 4) { q = 0; i = c; }
    else if (c < 36) { q = 1 + ((c - 4) & 7); i = (c - 4) >> 3; }
    else { q = 9 + (c - 36) % 7; i = (c - 36) / 7; }
    cg = i; rb = q & 7; br = q >> 3;
  }
  const int cta = e + 2 * cg + 8 * rb + 64 * br;
  const uint32_t bar_full1 = sb + OFF_BAR, bar_empty1 = bar_full1 + 64, bar_full2 = bar_full1 + 128,
                 bar_empty2 = bar_full1 + 160, bar_x = bar_full1 + 192  , bar_o_full = bar_full1 + 272,
                 bar_o_empty = bar_full1 + 280, bar_o = bar_full1 + 288  ;

  if (threadIdx.x == 0) TS(0);
  if (warp == 8 && lane == 0) {
    if (sb & 1023) __trap();
    prefetch_tmap(&tm.x[br]); prefetch_tmap(&tm.w[br]);
    for (int s = 0; s < G1_STAGES; s++) { mbar_init(bar_full1 + 8 * s, 1); mbar_init(bar_empty1 + 8 * s, 16); }
    for (int s = 0; s < G2_STAGES; s++) { mbar_init(bar_full2 + 8 * s, 1); mbar_init(bar_empty2 + 8 * s, 16); }
    for (int s = 0; s < 9; s++) mbar_init(bar_x + 8 * s, s == 0 ? 2 : 1);
    mbar_init(bar_o_full, 8); mbar_init(bar_o_empty, 2);
    for (int t = 0; t < 4; t++) mbar_init(bar_o + 8 * t, 1);
    asm volatile("fence.mbarrier_init.release.cluster;" ::: "memory");
    fence_async_smem();
    for (int it = 0; it < G1_STAGES; it++) {
      const int s = (it + 1) % G1_STAGES;
      mbar_expect_tx(bar_full1 + 8 * s, G1_STAGE);
      tma_load_2d(sb + s * G1_STAGE, &tm.x[br], e * 1024 + it * 64, rb * 128, bar_full1 + 8 * s);
    }
  }
  __syncwarp();
  asm volatile("barrier.cluster.arrive.relaxed.aligned;\nbarrier.cluster.wait.aligned;" ::: "memory");

  if (warp < 8) {
    asm volatile("setmaxnreg.inc.sync.aligned.u32 232;");
    const int wg = warp >> 2;
    float acc[128];
    uint32_t pk[48];
    float of[8][4];
    uint32_t xp[8];
    float pe[4][2];
    uint32_t b_lo[4], b_hi[4];
    const bool rel_any = lane < 2;
    const uint32_t rel_base = mapa(bar_full1, lane == 0 ? e : (e ^ 1));
    const int g = lane >> 2, tq = lane & 3;
    const bool use_lo0 = (2 * tq) > g, use_lo1 = (2 * tq + 1) > g;
    const uint32_t lo_mask = (use_lo0 ? 0xffffu : 0u) | (use_lo1 ? 0xffff0000u : 0u);
    const bool seq_start = (rb == 0 && warp == 0);
    const uint32_t slot = sb + OFF_X + warp * 2048;
    int s = 1, ph = 0;
    int kcount = 0; (void)kcount; unsigned kc[4]; (void)kc;

    enum { NONE = -1, XHI = 0, XLO = 1, RD = 2, QK = 3, SM = 4, PV = 5, ST = 6, SM1 = 7, SM2 = 8 };
    auto attn = [&](auto phase, int ta) {
      constexpr int P = decltype(phase)::value;
      if constexpr (P == XHI) {
#pragma unroll
        for (int i = 1; i < 16; i += 2) pk[32 + i] = movm_t(pk[32 + i]);
        if (ta > 0) mbar_wait(bar_o_empty, (ta - 1) & 1);
#pragma unroll
        for (int i = 0; i < 4; i++)
          sts128(slot + 2048 + i * 512 + lane * 16, pk[17 + 8 * i], pk[19 + 8 * i], pk[21 + 8 * i], pk[23 + 8 * i]);
        __syncwarp();
        if (lane == 0) mbar_arrive(bar_x + 8 * (warp + 1));
      } else if constexpr (P == XLO) {
#pragma unroll
        for (int i = 0; i < 16; i += 2) pk[32 + i] = movm_t(pk[32 + i]);
      } else if constexpr (P == RD) {
        mbar_wait(bar_x + 8 * warp, ta & 1);
        const uint4 k0 = lds128(slot + lane * 16), k1 = lds128(slot + 512 + lane * 16);
        xp[0] = k0.x; xp[1] = k0.y; xp[2] = k0.z; xp[3] = k0.w; xp[4] = k1.x; xp[5] = k1.y; xp[6] = k1.z; xp[7] = k1.w;
      } else if constexpr (P == QK) {
#pragma unroll
        for (int h = 0; h < 2; h++) {
          mma_init(of[3 * h], pk[8 * h], pk[8 * h + 1], pk[8 * h + 2], pk[8 * h + 3], xp[4 * h], xp[4 * h + 1]);
          mma_init(of[3 * h + 1], pk[8 * h], pk[8 * h + 1], pk[8 * h + 2], pk[8 * h + 3], pk[16 + 8 * h], pk[18 + 8 * h]);
          mma_init(of[3 * h + 2], pk[8 * h], pk[8 * h + 1], pk[8 * h + 2], pk[8 * h + 3], pk[17 + 8 * h], pk[19 + 8 * h]);
        }
#pragma unroll
        for (int h = 0; h < 2; h++) {
          mma_acc(of[3 * h], pk[8 * h + 4], pk[8 * h + 5], pk[8 * h + 6], pk[8 * h + 7], xp[4 * h + 2], xp[4 * h + 3]);
          mma_acc(of[3 * h + 1], pk[8 * h + 4], pk[8 * h + 5], pk[8 * h + 6], pk[8 * h + 7], pk[20 + 8 * h], pk[22 + 8 * h]);
          mma_acc(of[3 * h + 2], pk[8 * h + 4], pk[8 * h + 5], pk[8 * h + 6], pk[8 * h + 7], pk[21 + 8 * h], pk[23 + 8 * h]);
        }
      } else if constexpr (P == SM || P == SM1 || P == SM2) {
        if constexpr (P != SM2) {
          if (seq_start) of[0][0] = of[0][1] = of[3][0] = of[3][1] = -INFINITY;
          const float lo[4][2] = {{of[0][0], of[0][1]}, {of[1][2], of[1][3]}, {of[3][0], of[3][1]}, {of[4][2], of[4][3]}};
          const float hi[4][2] = {{of[1][0], of[1][1]}, {of[2][2], of[2][3]}, {of[4][0], of[4][1]}, {of[5][2], of[5][3]}};
          softmax_exp<4>(lo, hi, use_lo0, use_lo1, pe);
        }
        if constexpr (P != SM1) {
          const uint4 v0 = lds128(slot + 1024 + lane * 16), v1 = lds128(slot + 1536 + lane * 16);
          xp[0] = v0.x; xp[1] = v0.y; xp[2] = v0.z; xp[3] = v0.w; xp[4] = v1.x; xp[5] = v1.y; xp[6] = v1.z; xp[7] = v1.w;
          softmax_norm<4>(pe, lo_mask, b_lo, b_hi);
        }
      } else if constexpr (P == PV) {
#pragma unroll
        for (int h = 0; h < 2; h++) {
          mma_init(of[4 * h], xp[4 * h], xp[4 * h + 1], pk[32 + 8 * h], pk[34 + 8 * h], b_lo[2 * h], b_hi[2 * h]);
          mma_init(of[4 * h + 1], xp[4 * h + 2], xp[4 * h + 3], pk[36 + 8 * h], pk[38 + 8 * h], b_lo[2 * h], b_hi[2 * h]);
          mma_init(of[4 * h + 2], pk[32 + 8 * h], pk[34 + 8 * h], pk[33 + 8 * h], pk[35 + 8 * h], b_lo[2 * h + 1], b_hi[2 * h + 1]);
          mma_init(of[4 * h + 3], pk[36 + 8 * h], pk[38 + 8 * h], pk[37 + 8 * h], pk[39 + 8 * h], b_lo[2 * h + 1], b_hi[2 * h + 1]);
        }
      } else if constexpr (P == ST) {
#pragma unroll
        for (int i = 0; i < 4; i++)
          stsm_x4_t(slot + ((i & 1) * 8 + (lane & 7)) * 128 + ((((i >> 1) * 4 + (lane >> 3)) ^ (lane & 7)) << 4),
                    pack_bf16(of[2 * i][0], of[2 * i][1]), pack_bf16(of[2 * i][2], of[2 * i][3]),
                    pack_bf16(of[2 * i + 1][0], of[2 * i + 1][1]), pack_bf16(of[2 * i + 1][2], of[2 * i + 1][3]));
        fence_async_smem();
        __syncwarp();
        if (lane == 0) mbar_arrive(bar_o_full);
      }
    };
    uint32_t rel = 0;
    auto kstep = [&](auto g2, auto pre0, auto post, auto burst1, bool first, bool do_attn, int ta, bool release, int next) {
      constexpr bool G2 = decltype(g2)::value;
      constexpr uint32_t STAGE = G2 ? G2_STAGE : G1_STAGE;
      constexpr uint64_t HALF = G2 ? 1024 : 768;
      const uint64_t da = desc_kmajor(sb + s * STAGE + wg * 8192);
      const uint64_t db = desc_mnmajor(sb + s * STAGE + A_BYTES);
      if constexpr (decltype(pre0)::value != NONE) { if (do_attn && wg == 0) attn(pre0, ta); }
      bar_sync(1 + wg);
      KS(0);
      wgmma_fence();
      if constexpr (G2) {
        wgmma_n256(acc, da, db, !first);
        wgmma_n256(acc, da + 2, db + 128, 1);
        wgmma_n256(acc, da + 4, db + HALF, 1);
        wgmma_n256(acc, da + 6, db + HALF + 128, 1);
      } else {
        wgmma_n192(acc, da, db, !first);
        wgmma_n192(acc, da + 2, db + 128, 1);
        wgmma_n192(acc, da + 4, db + HALF, 1);
        wgmma_n192(acc, da + 6, db + HALF + 128, 1);
      }
      wgmma_commit();
      const bool late = decltype(burst1)::value != NONE && do_attn && wg == 1;
      if (!late && !(next < 0 && wg == 1)) bar_arrive(2 - wg);
      if (rel) mbar_arrive_cluster(rel);
      rel = (release && rel_any) ? rel_base + (G2 ? 160 : 64) + 8 * s : 0;
      KS(1);
      if constexpr (decltype(post)::value != NONE) { if (do_attn) attn(post, ta); }
      if (++s == (G2 ? G2_STAGES : G1_STAGES)) s = 0;
      if (s == (G2 ? 0 : 1)) ph ^= 1;
      if (!G2 && next == 1) { s = 0; ph = 0; }
      if (next >= 0) mbar_wait((next ? bar_full2 : bar_full1) + 8 * s, ph);
      if constexpr (decltype(burst1)::value != NONE) { if (late) { attn(burst1, ta); bar_arrive(1); } }
      KS(2);
      wgmma_wait<0>();
      KS(3); kcount++;
    };
    using F = std::false_type; using T = std::true_type;
#define PH(n) std::integral_constant<int, n>{}
    if (wg == 1) bar_arrive(1);
    mbar_wait(bar_full1 + 8 * s, ph);
    if (threadIdx.x == 0) TS(1);

#pragma unroll 1
    for (int t = 0; t < 4; t++) {
      const bool at = t > 0;
      kstep(F{}, PH(NONE), PH(NONE), PH(NONE), true, false, 0, true, 0);
      kstep(F{}, PH(NONE), PH(XHI), PH(NONE), false, at, t - 1, true, 0);
      kstep(F{}, PH(NONE), PH(XLO), PH(NONE), false, at, t - 1, true, 0);
#pragma unroll 1
      for (int ks = 3; ks < 6; ks++) kstep(F{}, PH(NONE), PH(NONE), PH(NONE), false, false, 0, true, 0);
      kstep(F{}, PH(NONE), PH(RD), PH(QK), false, at, t - 1, true, 0);
      kstep(F{}, PH(QK), PH(SM1), PH(NONE), false, at, t - 1, true, 0);
      kstep(F{}, PH(NONE), PH(SM2), PH(PV), false, at, t - 1, true, 0);
      kstep(F{}, PH(PV), PH(ST), PH(NONE), false, at, t - 1, true, 0);
      if (threadIdx.x == 0) TS(3 + 2 * t);
#pragma unroll 1
      for (int ks = 10; ks < 16; ks++) kstep(F{}, PH(NONE), PH(NONE), PH(NONE), false, false, 0, true, t == 3 && ks == 15);
      fence_acc<96>(acc);
#pragma unroll
      for (int i = 0; i < 48; i++) pk[i] = pack_bf16(acc[2 * i], acc[2 * i + 1]);
      if (threadIdx.x == 0) TS(2 + 2 * t);
    }
    kstep(T{}, PH(NONE), PH(XHI), PH(NONE), true, true, 3, true, 1);
    kstep(T{}, PH(NONE), PH(XLO), PH(NONE), false, true, 3, true, 1);
    kstep(T{}, PH(NONE), PH(NONE), PH(NONE), false, true, 3, true, 1);
    kstep(T{}, PH(NONE), PH(RD), PH(QK), false, true, 3, true, 1);
    kstep(T{}, PH(QK), PH(SM), PH(PV), false, true, 3, true, 1);
    kstep(T{}, PH(PV), PH(ST), PH(NONE), false, true, 3, true, 1);
    if (threadIdx.x == 0) TS(12);
#pragma unroll 1
    for (int ks = 6; ks < 16; ks++)
      kstep(T{}, PH(NONE), PH(NONE), PH(NONE), false, false, 0, ks < 16 - G2_STAGES, ks == 15 ? -1 : 1);
    fence_acc<128>(acc);
    if (threadIdx.x == 0) TS(10);
    {
      const uint32_t stg = sb + wg * G2_STAGE + (warp & 3) * 8192;
      const int r = ((lane >> 3) & 1) * 8 + (lane & 7);
#pragma unroll
      for (int c = 0; c < 4; c++) {
#pragma unroll
        for (int jj = 0; jj < 8; jj += 2) {
          const int j = c * 8 + jj;
          const uint32_t addr = stg + c * 2048 + r * 128 + (((jj + (lane >> 4)) ^ (r & 7)) << 4);
          stsm_x4(addr, pack_bf16(acc[4 * j], acc[4 * j + 1]), pack_bf16(acc[4 * j + 2], acc[4 * j + 3]),
                  pack_bf16(acc[4 * j + 4], acc[4 * j + 5]), pack_bf16(acc[4 * j + 6], acc[4 * j + 7]));
        }
        fence_async_smem();
        __syncwarp();
        if (lane == 0) {
          tma_store_2d(&tm.out, e * 2048 + br * 1024 + cg * 256 + c * 64, rb * 128 + warp * 16, stg + c * 2048);
          bulk_commit();
        }
      }
      if (lane == 0) bulk_wait0_read();
      if (threadIdx.x == 0) { atomicAdd(&g_epoch[cta], 1u); TS(11); }
      if (threadIdx.x == 128) TS(13);
    }
  } else {
    asm volatile("setmaxnreg.dec.sync.aligned.u32 40;");
    if (warp == 8) {
      if (lane == 0) {
        int s = 1, ph = 1;
        for (int it = 0; it < 64; it++) {
          const int ks = it & 15, hp = cg * 4 + (it >> 4);
          const uint32_t st = sb + s * G1_STAGE, fb = bar_full1 + 8 * s;
          if (it >= G1_STAGES) {
            mbar_wait(bar_empty1 + 8 * s, ph);
            mbar_expect_tx(fb, G1_STAGE);
            tma_load_2d(st, &tm.x[br], e * 1024 + ks * 64, rb * 128, fb);
          }
          tma_load_3d_mc(st + A_BYTES + e * 12288, &tm.w[br], hp * 64, ks * 64 + e * 32, 0, fb, (uint16_t)3);
          if (it == 8) { prefetch_tmap(&tm.wo[br]); prefetch_tmap(&tm.o); prefetch_tmap(&tm.out); }
          if (++s == G1_STAGES) s = 0;
          if (s == 1) ph ^= 1;
        }
        for (int it = 0; it < 16; it++) {
          const int kb = (it & 3) * 4 + (it >> 2), s2 = it & 3;
          const uint32_t st = sb + s2 * G2_STAGE, fb = bar_full2 + 8 * s2;
          if (it < G2_STAGES) {
            if (it == 0) mbar_wait(bar_empty1, 1);
            mbar_wait(bar_empty1 + 8 * (it + 1), 0);
          } else {
            mbar_wait(bar_empty2 + 8 * s2, ((it >> 2) - 1) & 1);
          }
          mbar_expect_tx(fb, G2_STAGE);
          tma_load_3d_mc(st + A_BYTES + e * 16384, &tm.wo[br], 0, kb * 64 + e * 32, cg * 4, fb, (uint16_t)3);
          if ((it & 3) == 0) mbar_wait(bar_o + 8 * (it >> 2), 0);
          tma_load_2d(st, &tm.o, kb * 64, (br * 2 + e) * 1024 + rb * 128, fb);
        }
      }
    } else {
      const unsigned tag = __ldcg(&g_epoch[cta]) + 1u;
      if (warp < 11) {
        const int half = 10 - warp;
        for (int t = 0; t < 4; t++) {
          mbar_wait(bar_x + (warp == 9 ? 64 : 8), t & 1);
          if (warp == 9) {
            if (rb < 7) {
              ulonglong2* dst = g_halo + ((cta + 8) * 4 + t) * 256 + lane;
              const unsigned long long hi = (unsigned long long)tag << 32;
#pragma unroll
              for (int i = 0; i < 4; i++) {
                const uint4 v = lds128(sb + OFF_X + 8 * 2048 + i * 512 + lane * 16);
                asm volatile("st.relaxed.gpu.global.v2.b64 [%0], {%1, %2};" ::"l"(dst + i * 64), "l"(hi | v.x), "l"(hi | v.y) : "memory");
                asm volatile("st.relaxed.gpu.global.v2.b64 [%0], {%1, %2};" ::"l"(dst + i * 64 + 32), "l"(hi | v.z), "l"(hi | v.w) : "memory");
              }
            }
            __syncwarp();
            if (lane == 0) mbar_arrive(bar_o_empty);
          }
          const ulonglong2* src = g_halo + (cta * 4 + t) * 256 + half * 128 + lane;
          unsigned long long v[8];
          if (rb > 0) {
            uint32_t spins = 0;
            while (true) {
#pragma unroll
              for (int p = 0; p < 4; p++)
                asm volatile("ld.relaxed.gpu.global.v2.b64 {%0, %1}, [%2];" : "=l"(v[2 * p]), "=l"(v[2 * p + 1])
                             : "l"(src + p * 32) : "memory");
              bool ok = true;
#pragma unroll
              for (int p = 0; p < 8; p++) ok &= (unsigned)(v[p] >> 32) == tag;
              if (__all_sync(0xffffffffu, ok)) break;
              if (++spins > SPIN_LIMIT) __trap();
            }
          } else {
#pragma unroll
            for (int p = 0; p < 8; p++) v[p] = 0;
          }
#pragma unroll
          for (int i = 0; i < 2; i++)
            sts128(sb + OFF_X + (half * 2 + i) * 512 + lane * 16, (uint32_t)v[4 * i], (uint32_t)v[4 * i + 1], (uint32_t)v[4 * i + 2], (uint32_t)v[4 * i + 3]);
          __syncwarp();
          if (lane == 0) { mbar_arrive(bar_x); if (warp == 9) TS(28 + t); }
        }
      } else if (lane == 0) {
        for (int t = 0; t < 4; t++) {
          mbar_wait(bar_o_full, t & 1);
          TS(16 + t);
          unsigned* flag = &g_o_ready[((br * 8 + rb) * 2 + e) * 4 + t];
          tma_store_2d(&tm.o, (cg * 4 + t) * 64, (br * 2 + e) * 1024 + rb * 128, sb + OFF_X);
          bulk_commit();
          bulk_wait0();
          mbar_arrive(bar_o_empty);
          asm volatile("red.release.gpu.global.add.u32 [%0], 1;" ::"l"(flag) : "memory");
          TS(20 + t);
          wait_flag(flag, tag * 4u);
          asm volatile("fence.proxy.async.global;" ::: "memory");
          mbar_arrive(bar_o + 8 * t);
          TS(24 + t);
        }
      }
    }
  }
}

typedef CUresult (*EncodeFn)(CUtensorMap*, CUtensorMapDataType, cuuint32_t, void*, const cuuint64_t*, const cuuint64_t*,
                             const cuuint32_t*, const cuuint32_t*, CUtensorMapInterleave, CUtensorMapSwizzle,
                             CUtensorMapL2promotion, CUtensorMapFloatOOBfill);

bool encode(EncodeFn fn, CUtensorMap* m, const void* ptr, int rank, const cuuint64_t* dims, const cuuint64_t* strides,
            const cuuint32_t* box) {
  const cuuint32_t es[3] = {1, 1, 1};
  return fn(m, CU_TENSOR_MAP_DATA_TYPE_BFLOAT16, rank, const_cast<void*>(ptr), dims, strides, box, es,
            CU_TENSOR_MAP_INTERLEAVE_NONE, CU_TENSOR_MAP_SWIZZLE_128B, CU_TENSOR_MAP_L2_PROMOTION_L2_256B,
            CU_TENSOR_MAP_FLOAT_OOB_FILL_NONE) == CUDA_SUCCESS;
}

}

extern "C" void kernel_launch(void* const* d_in, const int* in_sizes, int n_in, void* d_out, int out_size) {
  (void)in_sizes; (void)n_in; (void)out_size;
  void* fp = nullptr;
  cudaDriverEntryPointQueryResult qr;
  if (cudaGetDriverEntryPoint("cuTensorMapEncodeTiled", &fp, cudaEnableDefault, &qr) != cudaSuccess || !fp) return;
  EncodeFn fn = (EncodeFn)fp;
  void* o_ptr = nullptr;
  cudaGetSymbolAddress(&o_ptr, g_o);
  TMaps tm;
  bool ok = true;
  for (int b = 0; b < 2; b++) {
    {
      const cuuint64_t dims[2] = {2048, 1024}, str[1] = {4096};
      const cuuint32_t box[2] = {64, 128};
      ok &= encode(fn, &tm.x[b], d_in[3 * b + 0], 2, dims, str, box);
    }
    {
      const cuuint64_t dims[3] = {1024, 1024, 3}, str[2] = {6144, 2048};
      const cuuint32_t box[3] = {64, 32, 3};
      ok &= encode(fn, &tm.w[b], d_in[3 * b + 1], 3, dims, str, box);
    }
    {
      const cuuint64_t dims[3] = {64, 1024, 16}, str[2] = {2048, 128};
      const cuuint32_t box[3] = {64, 32, 4};
      ok &= encode(fn, &tm.wo[b], d_in[3 * b + 2], 3, dims, str, box);
    }
  }
  {
    const cuuint64_t dims[2] = {1024, 4096}, str[1] = {2048};
    const cuuint32_t box[2] = {64, 128};
    ok &= encode(fn, &tm.o, o_ptr, 2, dims, str, box);
  }
  {
    const cuuint64_t dims[2] = {4096, 1024}, str[1] = {8192};
    const cuuint32_t box[2] = {64, 16};
    ok &= encode(fn, &tm.out, d_out, 2, dims, str, box);
  }
  if (!ok) return;
  cudaFuncSetAttribute(fused_kernel, cudaFuncAttributeMaxDynamicSharedMemorySize, SMEM_BYTES);
  fused_kernel<<<NUM_CTAS, NUM_THREADS, SMEM_BYTES>>>(tm);
}
```

```cpp
#include <cuda_runtime.h>
#include <cuda_bf16.h>
#include <cuda.h>
#include <stdint.h>
#include <type_traits>

namespace {

__device__ __forceinline__ void wgmma_n192(float (&d)[128], uint64_t da, uint64_t db, int scale_d) {
  asm volatile("{\n.reg .pred p;\nsetp.ne.b32 p, %98, 0;\n"
    "wgmma.mma_async.sync.aligned.m64n192k16.f32.bf16.bf16 "
    "{%0, %1, %2, %3, %4, %5, %6, %7, %8, %9, %10, %11, %12, %13, %14, %15, "
    "%16, %17, %18, %19, %20, %21, %22, %23, %24, %25, %26, %27, %28, %29, %30, %31, "
    "%32, %33, %34, %35, %36, %37, %38, %39, %40, %41, %42, %43, %44, %45, %46, %47, "
    "%48, %49, %50, %51, %52, %53, %54, %55, %56, %57, %58, %59, %60, %61, %62, %63, "
    "%64, %65, %66, %67, %68, %69, %70, %71, %72, %73, %74, %75, %76, %77, %78, %79, "
    "%80, %81, %82, %83, %84, %85, %86, %87, %88, %89, %90, %91, %92, %93, %94, %95}, "
    "%96, %97, p, 1, 1, 0, 1;\n}\n"
    : "+f"(d[0]), "+f"(d[1]), "+f"(d[2]), "+f"(d[3]), "+f"(d[4]), "+f"(d[5]), "+f"(d[6]), "+f"(d[7]),
      "+f"(d[8]), "+f"(d[9]), "+f"(d[10]), "+f"(d[11]), "+f"(d[12]), "+f"(d[13]), "+f"(d[14]), "+f"(d[15]),
      "+f"(d[16]), "+f"(d[17]), "+f"(d[18]), "+f"(d[19]), "+f"(d[20]), "+f"(d[21]), "+f"(d[22]), "+f"(d[23]),
      "+f"(d[24]), "+f"(d[25]), "+f"(d[26]), "+f"(d[27]), "+f"(d[28]), "+f"(d[29]), "+f"(d[30]), "+f"(d[31]),
      "+f"(d[32]), "+f"(d[33]), "+f"(d[34]), "+f"(d[35]), "+f"(d[36]), "+f"(d[37]), "+f"(d[38]), "+f"(d[39]),
      "+f"(d[40]), "+f"(d[41]), "+f"(d[42]), "+f"(d[43]), "+f"(d[44]), "+f"(d[45]), "+f"(d[46]), "+f"(d[47]),
      "+f"(d[48]), "+f"(d[49]), "+f"(d[50]), "+f"(d[51]), "+f"(d[52]), "+f"(d[53]), "+f"(d[54]), "+f"(d[55]),
      "+f"(d[56]), "+f"(d[57]), "+f"(d[58]), "+f"(d[59]), "+f"(d[60]), "+f"(d[61]), "+f"(d[62]), "+f"(d[63]),
      "+f"(d[64]), "+f"(d[65]), "+f"(d[66]), "+f"(d[67]), "+f"(d[68]), "+f"(d[69]), "+f"(d[70]), "+f"(d[71]),
      "+f"(d[72]), "+f"(d[73]), "+f"(d[74]), "+f"(d[75]), "+f"(d[76]), "+f"(d[77]), "+f"(d[78]), "+f"(d[79]),
      "+f"(d[80]), "+f"(d[81]), "+f"(d[82]), "+f"(d[83]), "+f"(d[84]), "+f"(d[85]), "+f"(d[86]), "+f"(d[87]),
      "+f"(d[88]), "+f"(d[89]), "+f"(d[90]), "+f"(d[91]), "+f"(d[92]), "+f"(d[93]), "+f"(d[94]), "+f"(d[95])
    : "l"(da), "l"(db), "r"(scale_d));
}

__device__ __forceinline__ void wgmma_n256(float (&d)[128], uint64_t da, uint64_t db, int scale_d) {
  asm volatile("{\n.reg .pred p;\nsetp.ne.b32 p, %130, 0;\n"
    "wgmma.mma_async.sync.aligned.m64n256k16.f32.bf16.bf16 "
    "{%0, %1, %2, %3, %4, %5, %6, %7, %8, %9, %10, %11, %12, %13, %14, %15, "
    "%16, %17, %18, %19, %20, %21, %22, %23, %24, %25, %26, %27, %28, %29, %30, %31, "
    "%32, %33, %34, %35, %36, %37, %38, %39, %40, %41, %42, %43, %44, %45, %46, %47, "
    "%48, %49, %50, %51, %52, %53, %54, %55, %56, %57, %58, %59, %60, %61, %62, %63, "
    "%64, %65, %66, %67, %68, %69, %70, %71, %72, %73, %74, %75, %76, %77, %78, %79, "
    "%80, %81, %82, %83, %84, %85, %86, %87, %88, %89, %90, %91, %92, %93, %94, %95, "
    "%96, %97, %98, %99, %100, %101, %102, %103, %104, %105, %106, %107, %108, %109, %110, %111, "
    "%112, %113, %114, %115, %116, %117, %118, %119, %120, %121, %122, %123, %124, %125, %126, %127}, "
    "%128, %129, p, 1, 1, 0, 1;\n}\n"
    : "+f"(d[0]), "+f"(d[1]), "+f"(d[2]), "+f"(d[3]), "+f"(d[4]), "+f"(d[5]), "+f"(d[6]), "+f"(d[7]),
      "+f"(d[8]), "+f"(d[9]), "+f"(d[10]), "+f"(d[11]), "+f"(d[12]), "+f"(d[13]), "+f"(d[14]), "+f"(d[15]),
      "+f"(d[16]), "+f"(d[17]), "+f"(d[18]), "+f"(d[19]), "+f"(d[20]), "+f"(d[21]), "+f"(d[22]), "+f"(d[23]),
      "+f"(d[24]), "+f"(d[25]), "+f"(d[26]), "+f"(d[27]), "+f"(d[28]), "+f"(d[29]), "+f"(d[30]), "+f"(d[31]),
      "+f"(d[32]), "+f"(d[33]), "+f"(d[34]), "+f"(d[35]), "+f"(d[36]), "+f"(d[37]), "+f"(d[38]), "+f"(d[39]),
      "+f"(d[40]), "+f"(d[41]), "+f"(d[42]), "+f"(d[43]), "+f"(d[44]), "+f"(d[45]), "+f"(d[46]), "+f"(d[47]),
      "+f"(d[48]), "+f"(d[49]), "+f"(d[50]), "+f"(d[51]), "+f"(d[52]), "+f"(d[53]), "+f"(d[54]), "+f"(d[55]),
      "+f"(d[56]), "+f"(d[57]), "+f"(d[58]), "+f"(d[59]), "+f"(d[60]), "+f"(d[61]), "+f"(d[62]), "+f"(d[63]),
      "+f"(d[64]), "+f"(d[65]), "+f"(d[66]), "+f"(d[67]), "+f"(d[68]), "+f"(d[69]), "+f"(d[70]), "+f"(d[71]),
      "+f"(d[72]), "+f"(d[73]), "+f"(d[74]), "+f"(d[75]), "+f"(d[76]), "+f"(d[77]), "+f"(d[78]), "+f"(d[79]),
      "+f"(d[80]), "+f"(d[81]), "+f"(d[82]), "+f"(d[83]), "+f"(d[84]), "+f"(d[85]), "+f"(d[86]), "+f"(d[87]),
      "+f"(d[88]), "+f"(d[89]), "+f"(d[90]), "+f"(d[91]), "+f"(d[92]), "+f"(d[93]), "+f"(d[94]), "+f"(d[95]),
      "+f"(d[96]), "+f"(d[97]), "+f"(d[98]), "+f"(d[99]), "+f"(d[100]), "+f"(d[101]), "+f"(d[102]), "+f"(d[103]),
      "+f"(d[104]), "+f"(d[105]), "+f"(d[106]), "+f"(d[107]), "+f"(d[108]), "+f"(d[109]), "+f"(d[110]), "+f"(d[111]),
      "+f"(d[112]), "+f"(d[113]), "+f"(d[114]), "+f"(d[115]), "+f"(d[116]), "+f"(d[117]), "+f"(d[118]), "+f"(d[119]),
      "+f"(d[120]), "+f"(d[121]), "+f"(d[122]), "+f"(d[123]), "+f"(d[124]), "+f"(d[125]), "+f"(d[126]), "+f"(d[127])
    : "l"(da), "l"(db), "r"(scale_d));
}

template <int O>
__device__ __forceinline__ void wgmma_n128(float (&d)[128], uint64_t da, uint64_t db, int scale_d) {
  asm volatile("{\n.reg .pred p;\nsetp.ne.b32 p, %66, 0;\n"
    "wgmma.mma_async.sync.aligned.m64n128k16.f32.bf16.bf16 "
    "{%0, %1, %2, %3, %4, %5, %6, %7, %8, %9, %10, %11, %12, %13, %14, %15, "
    "%16, %17, %18, %19, %20, %21, %22, %23, %24, %25, %26, %27, %28, %29, %30, %31, "
    "%32, %33, %34, %35, %36, %37, %38, %39, %40, %41, %42, %43, %44, %45, %46, %47, "
    "%48, %49, %50, %51, %52, %53, %54, %55, %56, %57, %58, %59, %60, %61, %62, %63}, "
    "%64, %65, p, 1, 1, 0, 1;\n}\n"
    : "+f"(d[O + 0]), "+f"(d[O + 1]), "+f"(d[O + 2]), "+f"(d[O + 3]), "+f"(d[O + 4]), "+f"(d[O + 5]), "+f"(d[O + 6]), "+f"(d[O + 7]),
      "+f"(d[O + 8]), "+f"(d[O + 9]), "+f"(d[O + 10]), "+f"(d[O + 11]), "+f"(d[O + 12]), "+f"(d[O + 13]), "+f"(d[O + 14]), "+f"(d[O + 15]),
      "+f"(d[O + 16]), "+f"(d[O + 17]), "+f"(d[O + 18]), "+f"(d[O + 19]), "+f"(d[O + 20]), "+f"(d[O + 21]), "+f"(d[O + 22]), "+f"(d[O + 23]),
      "+f"(d[O + 24]), "+f"(d[O + 25]), "+f"(d[O + 26]), "+f"(d[O + 27]), "+f"(d[O + 28]), "+f"(d[O + 29]), "+f"(d[O + 30]), "+f"(d[O + 31]),
      "+f"(d[O + 32]), "+f"(d[O + 33]), "+f"(d[O + 34]), "+f"(d[O + 35]), "+f"(d[O + 36]), "+f"(d[O + 37]), "+f"(d[O + 38]), "+f"(d[O + 39]),
      "+f"(d[O + 40]), "+f"(d[O + 41]), "+f"(d[O + 42]), "+f"(d[O + 43]), "+f"(d[O + 44]), "+f"(d[O + 45]), "+f"(d[O + 46]), "+f"(d[O + 47]),
      "+f"(d[O + 48]), "+f"(d[O + 49]), "+f"(d[O + 50]), "+f"(d[O + 51]), "+f"(d[O + 52]), "+f"(d[O + 53]), "+f"(d[O + 54]), "+f"(d[O + 55]),
      "+f"(d[O + 56]), "+f"(d[O + 57]), "+f"(d[O + 58]), "+f"(d[O + 59]), "+f"(d[O + 60]), "+f"(d[O + 61]), "+f"(d[O + 62]), "+f"(d[O + 63])
    : "l"(da), "l"(db), "r"(scale_d));
}

#define PFL 1
#define PFD 0
#define START_DELAY 400
#define START_AT 1
#define START_P 4
#define START_PW 5
#define O_SLEEP 80
#define O_SLEEP3 50
constexpr int NUM_CTAS = 128;
constexpr int NUM_THREADS = 384;
constexpr int G1_STAGES = 5, G2_STAGES = 4;
constexpr uint32_t A_BYTES = 16384;
constexpr uint32_t G1_STAGE = 40960;
constexpr uint32_t G2_STAGE = 49152;
constexpr uint32_t RING_BYTES = G1_STAGES * G1_STAGE;
constexpr uint32_t OFF_X = RING_BYTES;
constexpr uint32_t OFF_BAR = OFF_X + 9 * 2048;
constexpr uint32_t SMEM_BYTES = OFF_BAR + 512;
constexpr uint32_t SPIN_LIMIT = 1u << 24;

struct alignas(64) TMaps {
  CUtensorMap x[2], w[2], wo[2], out, x0[2], w0[2];
  const void* xp[2];
  const void* wp[2];
};

__device__ uint4 g_o[32 * 16 * 1024];
__device__ ulonglong2 g_halo[NUM_CTAS * 4 * 256];
__device__ unsigned g_o_ready[32 * 4];
__device__ unsigned g_epoch[NUM_CTAS];
#define TS(slot)
#define KS(i)

__device__ __forceinline__ void mbar_init(uint32_t bar, uint32_t count) {
  asm volatile("mbarrier.init.shared::cta.b64 [%0], %1;" ::"r"(bar), "r"(count) : "memory");
}
__device__ __forceinline__ bool mbar_try_wait(uint32_t bar, uint32_t parity) {
  uint32_t ok;
  asm volatile("{\n.reg .pred p;\nmbarrier.try_wait.parity.shared::cta.b64 p, [%1], %2;\nselp.u32 %0, 1, 0, p;\n}\n"
               : "=r"(ok) : "r"(bar), "r"(parity) : "memory");
  return ok != 0;
}
__device__ __forceinline__ void mbar_wait(uint32_t bar, uint32_t parity) {
  uint32_t spins = 0;
  while (!mbar_try_wait(bar, parity)) { if (++spins > SPIN_LIMIT) __trap(); }
}
__device__ __forceinline__ void mbar_arrive(uint32_t bar) {
  asm volatile("mbarrier.arrive.shared::cta.b64 _, [%0];" ::"r"(bar) : "memory");
}
__device__ __forceinline__ void mbar_arrive_cluster(uint32_t bar_cluster_addr) {
  asm volatile("mbarrier.arrive.shared::cluster.b64 _, [%0];" ::"r"(bar_cluster_addr) : "memory");
}
__device__ __forceinline__ void mbar_expect_tx(uint32_t bar, uint32_t bytes) {
  asm volatile("mbarrier.arrive.expect_tx.shared::cta.b64 _, [%0], %1;" ::"r"(bar), "r"(bytes) : "memory");
}
__device__ __forceinline__ uint32_t mapa(uint32_t addr, uint32_t rank) {
  uint32_t r; asm("mapa.shared::cluster.u32 %0, %1, %2;" : "=r"(r) : "r"(addr), "r"(rank)); return r;
}
__device__ __forceinline__ void tma_load_2d(uint32_t dst, const CUtensorMap* m, int c0, int c1, uint32_t bar) {
  asm volatile("cp.async.bulk.tensor.2d.shared::cluster.global.mbarrier::complete_tx::bytes [%0], [%1, {%3, %4}], [%2];"
               ::"r"(dst), "l"(m), "r"(bar), "r"(c0), "r"(c1) : "memory");
}
__device__ __forceinline__ void tma_load_3d(uint32_t dst, const CUtensorMap* m, int c0, int c1, int c2, uint32_t bar) {
  asm volatile("cp.async.bulk.tensor.3d.shared::cluster.global.mbarrier::complete_tx::bytes [%0], [%1, {%3, %4, %5}], [%2];"
               ::"r"(dst), "l"(m), "r"(bar), "r"(c0), "r"(c1), "r"(c2) : "memory");
}
__device__ __forceinline__ void tma_load_3d_mc(uint32_t dst, const CUtensorMap* m, int c0, int c1, int c2, uint32_t bar, uint16_t mask) {
  asm volatile("cp.async.bulk.tensor.3d.shared::cluster.global.mbarrier::complete_tx::bytes.multicast::cluster [%0], [%1, {%3, %4, %5}], [%2], %6;"
               ::"r"(dst), "l"(m), "r"(bar), "r"(c0), "r"(c1), "r"(c2), "h"(mask) : "memory");
}
__device__ __forceinline__ void tma_store_2d(const CUtensorMap* m, int c0, int c1, uint32_t src) {
  asm volatile("cp.async.bulk.tensor.2d.global.shared::cta.bulk_group [%0, {%2, %3}], [%1];"
               ::"l"(m), "r"(src), "r"(c0), "r"(c1) : "memory");
}
__device__ __forceinline__ void bulk_load(uint32_t dst, const void* src, uint32_t bytes, uint32_t bar) {
  asm volatile("cp.async.bulk.shared::cluster.global.mbarrier::complete_tx::bytes [%0], [%1], %2, [%3];"
               ::"r"(dst), "l"(src), "r"(bytes), "r"(bar) : "memory");
}
__device__ __forceinline__ void bulk_store(void* dst, uint32_t src, uint32_t bytes) {
  asm volatile("cp.async.bulk.global.shared::cta.bulk_group [%0], [%1], %2;" ::"l"(dst), "r"(src), "r"(bytes) : "memory");
}
__device__ __forceinline__ void bulk_commit() { asm volatile("cp.async.bulk.commit_group;" ::: "memory"); }
__device__ __forceinline__ void bulk_wait0() { asm volatile("cp.async.bulk.wait_group 0;" ::: "memory"); }
__device__ __forceinline__ void bulk_wait0_read() { asm volatile("cp.async.bulk.wait_group.read 0;" ::: "memory"); }
__device__ __forceinline__ void fence_async_smem() { asm volatile("fence.proxy.async.shared::cta;" ::: "memory"); }
__device__ __forceinline__ void prefetch_tmap(const CUtensorMap* m) {
  asm volatile("prefetch.tensormap [%0];" ::"l"(m) : "memory");
}
__device__ __forceinline__ void wgmma_fence() { asm volatile("wgmma.fence.sync.aligned;" ::: "memory"); }
__device__ __forceinline__ void wgmma_commit() { asm volatile("wgmma.commit_group.sync.aligned;" ::: "memory"); }
template <int N> __device__ __forceinline__ void wgmma_wait() { asm volatile("wgmma.wait_group.sync.aligned %0;" ::"n"(N) : "memory"); }
template <int B, int N> __device__ __forceinline__ void fence_acc(float (&d)[128]) {
#pragma unroll
  for (int i = B; i < N; i++) asm volatile("" : "+f"(d[i])::"memory");
}
__device__ __forceinline__ void bar_sync(int id) { asm volatile("bar.sync %0, 256;" ::"r"(id) : "memory"); }
__device__ __forceinline__ void bar_arrive(int id) { asm volatile("bar.arrive %0, 256;" ::"r"(id) : "memory"); }
__device__ __forceinline__ void bar_arrive_after(int id, float dep, uint32_t zero) { bar_arrive(id + (__float_as_uint(dep) & zero)); }
__device__ __forceinline__ uint64_t desc_kmajor(uint32_t addr) {
  return (uint64_t)((addr & 0x3FFFF) >> 4) | (1ull << 16) | (64ull << 32) | (1ull << 62);
}
__device__ __forceinline__ uint64_t desc_mnmajor(uint32_t addr) {
  return (uint64_t)((addr & 0x3FFFF) >> 4) | (256ull << 16) | (64ull << 32) | (1ull << 62);
}
__device__ __forceinline__ uint32_t pack_bf16(float lo, float hi) {
  uint32_t r; asm("cvt.rn.bf16x2.f32 %0, %1, %2;" : "=r"(r) : "f"(hi), "f"(lo)); return r;
}
__device__ __forceinline__ void stsm_x4(uint32_t addr, uint32_t r0, uint32_t r1, uint32_t r2, uint32_t r3) {
  asm volatile("stmatrix.sync.aligned.m8n8.x4.shared.b16 [%0], {%1, %2, %3, %4};" ::"r"(addr), "r"(r0), "r"(r1), "r"(r2), "r"(r3) : "memory");
}
__device__ __forceinline__ void stsm_x4_t(uint32_t addr, uint32_t r0, uint32_t r1, uint32_t r2, uint32_t r3) {
  asm volatile("stmatrix.sync.aligned.m8n8.x4.trans.shared.b16 [%0], {%1, %2, %3, %4};" ::"r"(addr), "r"(r0), "r"(r1), "r"(r2), "r"(r3) : "memory");
}
__device__ __forceinline__ uint32_t movm_t(uint32_t a) {
  uint32_t d; asm volatile("movmatrix.sync.aligned.m8n8.trans.b16 %0, %1;" : "=r"(d) : "r"(a)); return d;
}
__device__ __forceinline__ void mma_init(float (&c)[4], uint32_t a0, uint32_t a1, uint32_t a2, uint32_t a3, uint32_t b0, uint32_t b1) {
  asm volatile("mma.sync.aligned.m16n8k16.row.col.f32.bf16.bf16.f32 {%0, %1, %2, %3}, {%4, %5, %6, %7}, {%8, %9}, {%10, %10, %10, %10};"
               : "=f"(c[0]), "=f"(c[1]), "=f"(c[2]), "=f"(c[3]) : "r"(a0), "r"(a1), "r"(a2), "r"(a3), "r"(b0), "r"(b1), "f"(0.f));
}
__device__ __forceinline__ void mma_acc(float (&c)[4], uint32_t a0, uint32_t a1, uint32_t a2, uint32_t a3, uint32_t b0, uint32_t b1) {
  asm volatile("mma.sync.aligned.m16n8k16.row.col.f32.bf16.bf16.f32 {%0, %1, %2, %3}, {%4, %5, %6, %7}, {%8, %9}, {%0, %1, %2, %3};"
               : "+f"(c[0]), "+f"(c[1]), "+f"(c[2]), "+f"(c[3]) : "r"(a0), "r"(a1), "r"(a2), "r"(a3), "r"(b0), "r"(b1));
}
__device__ __forceinline__ float ex2(float x) { float y; asm("ex2.approx.ftz.f32 %0, %1;" : "=f"(y) : "f"(x)); return y; }
__device__ __forceinline__ unsigned ld_acquire(const unsigned* p) {
  unsigned v; asm volatile("ld.acquire.gpu.global.u32 %0, [%1];" : "=r"(v) : "l"(p) : "memory"); return v;
}
__device__ __forceinline__ void wait_flag(const unsigned* p, unsigned target) {
  uint32_t spins = 0;
  while ((int)(ld_acquire(p) - target) < 0) { if (++spins > SPIN_LIMIT) __trap(); __nanosleep(20); }
}
__device__ __forceinline__ uint4 lds128(uint32_t addr) {
  uint4 v; asm volatile("ld.shared.v4.u32 {%0, %1, %2, %3}, [%4];" : "=r"(v.x), "=r"(v.y), "=r"(v.z), "=r"(v.w) : "r"(addr) : "memory"); return v;
}
__device__ __forceinline__ void sts128(uint32_t addr, uint32_t a, uint32_t b, uint32_t c, uint32_t d) {
  asm volatile("st.shared.v4.u32 [%0], {%1, %2, %3, %4};" ::"r"(addr), "r"(a), "r"(b), "r"(c), "r"(d) : "memory");
}

template <int N>
__device__ __forceinline__ void softmax_exp(const float (&lo)[N][2], const float (&hi)[N][2], bool use_lo0, bool use_lo1,
                                            float (&ex)[N][2]) {
  constexpr float kScale = 0.17677669529663687f * 1.4426950408889634f;
  float m[N];
#pragma unroll
  for (int i = 0; i < N; i++) { ex[i][0] = use_lo0 ? lo[i][0] : hi[i][0]; ex[i][1] = use_lo1 ? lo[i][1] : hi[i][1]; m[i] = fmaxf(ex[i][0], ex[i][1]); }
#pragma unroll
  for (int i = 0; i < N; i++) m[i] = fmaxf(m[i], __shfl_xor_sync(0xffffffffu, m[i], 1));
#pragma unroll
  for (int i = 0; i < N; i++) m[i] = fmaxf(m[i], __shfl_xor_sync(0xffffffffu, m[i], 2));
#pragma unroll
  for (int i = 0; i < N; i++) { ex[i][0] = ex2((ex[i][0] - m[i]) * kScale); ex[i][1] = ex2((ex[i][1] - m[i]) * kScale); }
}
template <int N>
__device__ __forceinline__ void softmax_norm(const float (&ex)[N][2], uint32_t lo_mask, uint32_t (&b_lo)[N], uint32_t (&b_hi)[N]) {
  float s[N];
#pragma unroll
  for (int i = 0; i < N; i++) s[i] = ex[i][0] + ex[i][1];
#pragma unroll
  for (int i = 0; i < N; i++) s[i] += __shfl_xor_sync(0xffffffffu, s[i], 1);
#pragma unroll
  for (int i = 0; i < N; i++) s[i] += __shfl_xor_sync(0xffffffffu, s[i], 2);
#pragma unroll
  for (int i = 0; i < N; i++) {
    float r;
    asm("rcp.approx.ftz.f32 %0, %1;" : "=f"(r) : "f"(s[i]));
    const uint32_t p = pack_bf16(ex[i][0] * r, ex[i][1] * r);
    b_lo[i] = p & lo_mask;
    b_hi[i] = p & ~lo_mask;
  }
}

__global__ void __cluster_dims__(2, 1, 1) __launch_bounds__(NUM_THREADS, 1)
fused_kernel(const __grid_constant__ TMaps tm) {
  extern __shared__ __align__(1024) uint8_t smem_raw[];
  const uint32_t sb = (uint32_t)__cvta_generic_to_shared(smem_raw);
  const int warp = __shfl_sync(0xffffffffu, threadIdx.x >> 5, 0), lane = threadIdx.x & 31;
  const int e = blockIdx.x & 1;
  int cg, rb, br;
  {
    const int c = blockIdx.x >> 1;
    int q, i;
    if (c < 4) { q = 0; i = c; }
    else if (c < 36) { q = 1 + ((c - 4) & 7); i = (c - 4) >> 3; }
    else { q = 9 + (c - 36) % 7; i = (c - 36) / 7; }
    cg = i; rb = q & 7; br = q >> 3;
  }
  const int cta = e + 2 * cg + 8 * rb + 64 * br;
  const uint32_t bar_full1 = sb + OFF_BAR, bar_empty1 = bar_full1 + 64, bar_full2 = bar_full1 + 128,
                 bar_empty2 = bar_full1 + 160, bar_o_full = bar_full1 + 192, bar_o_empty = bar_full1 + 200,
                 bar_o = bar_full1 + 208  , bar_x = bar_full1 + 240  ;

  if (threadIdx.x == 0) TS(0);
  if (warp == 8 && lane == 0) {
    if (START_P) prefetch_tmap(&tm.x0[br]);
    if (START_PW) prefetch_tmap(&tm.w0[br]);
    prefetch_tmap(&tm.x[br]); prefetch_tmap(&tm.w[br]);
    for (int s = 0; s < G1_STAGES; s++) mbar_init(bar_full1 + 8 * s, 1);
    asm volatile("fence.mbarrier_init.release.cluster;" ::: "memory");
  } else if (warp == 9 && lane == 0) {
    if (sb & 1023) __trap();
    for (int s = 0; s < G1_STAGES; s++) mbar_init(bar_empty1 + 8 * s, 16);
    for (int s = 0; s < G2_STAGES; s++) { mbar_init(bar_full2 + 8 * s, 1); mbar_init(bar_empty2 + 8 * s, 16); }
    for (int s = 0; s < 18; s++) mbar_init(bar_x + 8 * s, 1);
    mbar_init(bar_o_full, 8); mbar_init(bar_o_empty, 3);
    for (int t = 0; t < 4; t++) mbar_init(bar_o + 8 * t, 1);
    asm volatile("fence.mbarrier_init.release.cluster;" ::: "memory");
  }
  else if (warp < 8) {
    const int i = threadIdx.x;
    const int ks = i >> 6;
    if (ks < PFL) {
      if (PFD && ks > 0) { const long long c0 = clock64(); while (clock64() - c0 < PFD * ks) {} }
      if ((i & 63) < 32) {
        const char* p = (const char*)tm.xp[br] + (size_t)(rb * 128 + cg * 32 + lane) * 4096 + e * 2048 + ks * 128;
        asm volatile("prefetch.global.L2 [%0];" ::"l"(p));
      } else if (lane < 12) {
        const int l = rb * 2 + e + 16 * lane;
        const char* p = (const char*)tm.wp[br] + (size_t)(ks * 64 + l / 3) * 6144 + (l % 3) * 2048 + cg * 512;
        asm volatile("prefetch.global.L2 [%0];" ::"l"(p));
      }
    }
  }
  __syncwarp();
  asm volatile("barrier.cluster.arrive.relaxed.aligned;" ::: "memory");

  if (warp < 8) {
    asm volatile("setmaxnreg.inc.sync.aligned.u32 232;");
    asm volatile("barrier.cluster.wait.aligned;" ::: "memory");
    const int wg = warp >> 2;
    float acc[128], acc2[128];
    uint32_t pk[48];
    float of[8][4];
    uint32_t xp[8];
    float pe[4][2];
    uint32_t b_lo[4], b_hi[4];
    const bool rel_any = lane < 2;
    const uint32_t rel_base = mapa(bar_full1, lane == 0 ? e : (e ^ 1));
    const int g = lane >> 2, tq = lane & 3;
    const bool use_lo0 = (2 * tq) > g, use_lo1 = (2 * tq + 1) > g;
    const uint32_t lo_mask = (use_lo0 ? 0xffffu : 0u) | (use_lo1 ? 0xffff0000u : 0u);
    const bool seq_start = (rb == 0 && warp == 0);
    const uint32_t slot = sb + OFF_X + warp * 2048;
    int s = 1, ph = 0;
    int kcount = 0; (void)kcount; unsigned kc[4]; (void)kc;

    enum { XK = 1, MH = 2, XV = 4, ML = 8, RK = 16, S1 = 32, S2 = 64, RV = 128, ST0 = 256, ST1 = 512, QK = 1024, PV = 2048 };
    auto attn = [&](auto phase, int ta) __attribute__((always_inline)) {
      constexpr int P = decltype(phase)::value;
      if constexpr ((P & XK) != 0) {
        if (ta > 0) mbar_wait(bar_o_empty, (ta - 1) & 1);
        sts128(slot + 2048 + lane * 16, pk[17], pk[19], pk[21], pk[23]);
        sts128(slot + 2560 + lane * 16, pk[25], pk[27], pk[29], pk[31]);
        __syncwarp();
        if (lane == 0) mbar_arrive(bar_x + 16 * warp + 16);
      }
      if constexpr ((P & MH) != 0) {
#pragma unroll
        for (int i = 1; i < 16; i += 2) pk[32 + i] = movm_t(pk[32 + i]);
      }
      if constexpr ((P & XV) != 0) {
        sts128(slot + 3072 + lane * 16, pk[33], pk[35], pk[37], pk[39]);
        sts128(slot + 3584 + lane * 16, pk[41], pk[43], pk[45], pk[47]);
        __syncwarp();
        if (lane == 0) mbar_arrive(bar_x + 16 * warp + 24);
      }
      if constexpr ((P & ML) != 0) {
#pragma unroll
        for (int i = 0; i < 16; i += 2) pk[32 + i] = movm_t(pk[32 + i]);
      }
      if constexpr ((P & S1) != 0) {
        if (seq_start) of[0][0] = of[0][1] = of[3][0] = of[3][1] = -INFINITY;
        const float lo[4][2] = {{of[0][0], of[0][1]}, {of[1][2], of[1][3]}, {of[3][0], of[3][1]}, {of[4][2], of[4][3]}};
        const float hi[4][2] = {{of[1][0], of[1][1]}, {of[2][2], of[2][3]}, {of[4][0], of[4][1]}, {of[5][2], of[5][3]}};
        softmax_exp<4>(lo, hi, use_lo0, use_lo1, pe);
      }
      if constexpr ((P & S2) != 0) softmax_norm<4>(pe, lo_mask, b_lo, b_hi);
      if constexpr ((P & (RK | RV)) != 0) {
        constexpr int V = (P & RV) != 0;
        mbar_wait(bar_x + 16 * warp + 8 * V, ta & 1);
        const uint4 x0 = lds128(slot + V * 1024 + lane * 16), x1 = lds128(slot + V * 1024 + 512 + lane * 16);
        xp[0] = x0.x; xp[1] = x0.y; xp[2] = x0.z; xp[3] = x0.w; xp[4] = x1.x; xp[5] = x1.y; xp[6] = x1.z; xp[7] = x1.w;
      }
      if constexpr ((P & QK) != 0) {
#pragma unroll
        for (int h = 0; h < 2; h++) {
          mma_init(of[3 * h], pk[8 * h], pk[8 * h + 1], pk[8 * h + 2], pk[8 * h + 3], xp[4 * h], xp[4 * h + 1]);
          mma_init(of[3 * h + 1], pk[8 * h], pk[8 * h + 1], pk[8 * h + 2], pk[8 * h + 3], pk[16 + 8 * h], pk[18 + 8 * h]);
          mma_init(of[3 * h + 2], pk[8 * h], pk[8 * h + 1], pk[8 * h + 2], pk[8 * h + 3], pk[17 + 8 * h], pk[19 + 8 * h]);
        }
#pragma unroll
        for (int h = 0; h < 2; h++) {
          mma_acc(of[3 * h], pk[8 * h + 4], pk[8 * h + 5], pk[8 * h + 6], pk[8 * h + 7], xp[4 * h + 2], xp[4 * h + 3]);
          mma_acc(of[3 * h + 1], pk[8 * h + 4], pk[8 * h + 5], pk[8 * h + 6], pk[8 * h + 7], pk[20 + 8 * h], pk[22 + 8 * h]);
          mma_acc(of[3 * h + 2], pk[8 * h + 4], pk[8 * h + 5], pk[8 * h + 6], pk[8 * h + 7], pk[21 + 8 * h], pk[23 + 8 * h]);
        }
      }
      if constexpr ((P & PV) != 0) {
#pragma unroll
        for (int h = 0; h < 2; h++) {
          mma_init(of[4 * h], xp[4 * h], xp[4 * h + 1], pk[32 + 8 * h], pk[34 + 8 * h], b_lo[2 * h], b_hi[2 * h]);
          mma_init(of[4 * h + 1], xp[4 * h + 2], xp[4 * h + 3], pk[36 + 8 * h], pk[38 + 8 * h], b_lo[2 * h], b_hi[2 * h]);
          mma_init(of[4 * h + 2], pk[32 + 8 * h], pk[34 + 8 * h], pk[33 + 8 * h], pk[35 + 8 * h], b_lo[2 * h + 1], b_hi[2 * h + 1]);
          mma_init(of[4 * h + 3], pk[36 + 8 * h], pk[38 + 8 * h], pk[37 + 8 * h], pk[39 + 8 * h], b_lo[2 * h + 1], b_hi[2 * h + 1]);
        }
      }
      if constexpr ((P & (ST0 | ST1)) != 0) {
#pragma unroll
        for (int i = (P & ST0) ? 0 : 2; i < ((P & ST1) ? 4 : 2); i++)
          stsm_x4_t(slot + ((i & 1) * 8 + (lane & 7)) * 128 + ((((i >> 1) * 4 + (lane >> 3)) ^ (lane & 7)) << 4),
                    pack_bf16(of[2 * i][0], of[2 * i][1]), pack_bf16(of[2 * i][2], of[2 * i][3]),
                    pack_bf16(of[2 * i + 1][0], of[2 * i + 1][1]), pack_bf16(of[2 * i + 1][2], of[2 * i + 1][3]));
        if constexpr ((P & ST1) != 0) {
          fence_async_smem();
          __syncwarp();
          if (lane == 0) mbar_arrive(bar_o_full);
        }
      }
    };
    uint32_t rel = 0;
    auto kstep = [&](auto g2, auto pre0, auto post, auto burst1, bool first, bool do_attn, int ta, bool release, int next) __attribute__((always_inline)) {
      constexpr bool G2 = decltype(g2)::value;
      constexpr uint32_t STAGE = G2 ? G2_STAGE : G1_STAGE;
      constexpr uint64_t HALF = G2 ? 1024 : 768;
      const uint64_t da = desc_kmajor(sb + s * STAGE + wg * 8192);
      const uint64_t db = desc_mnmajor(sb + s * STAGE + A_BYTES);
      if constexpr (decltype(pre0)::value != 0) { if (do_attn && wg == 0) attn(pre0, ta); }
      bar_sync(1 + wg);
      KS(0);
      wgmma_fence();
      if constexpr (G2) {
        wgmma_n256(acc2, da, db, !first);
        wgmma_n256(acc2, da + 2, db + 128, 1);
        wgmma_n256(acc2, da + 4, db + HALF, 1);
        wgmma_n256(acc2, da + 6, db + HALF + 128, 1);
      } else {
        wgmma_n192(acc, da, db, !first);
        wgmma_n192(acc, da + 2, db + 128, 1);
        wgmma_n192(acc, da + 4, db + HALF, 1);
        wgmma_n192(acc, da + 6, db + HALF + 128, 1);
      }
      wgmma_commit();
      const bool late = decltype(burst1)::value != 0 && do_attn && wg == 1;
      if (!late && !(next < 0 && wg == 1)) bar_arrive(2 - wg);
      if (rel) mbar_arrive_cluster(rel);
      rel = (release && rel_any) ? rel_base + (G2 ? 160 : 64) + 8 * s : 0;
      KS(1);
      if constexpr (decltype(post)::value != 0) { if (do_attn) attn(post, ta); }
      if (++s == (G2 ? G2_STAGES : G1_STAGES)) s = 0;
      if (s == (G2 ? 0 : 1)) ph ^= 1;
      if (!G2 && next == 1) { s = 0; ph = 0; }
      if (next >= 0) mbar_wait((next ? bar_full2 : bar_full1) + 8 * s, ph);
      if constexpr (decltype(burst1)::value != 0) { if (late) { attn(burst1, ta); bar_arrive_after(1, of[decltype(burst1)::value == PV ? 4 : 2][0], blockIdx.y); } }
      KS(2);
      wgmma_wait<0>();
      KS(3); kcount++;
    };
    using F = std::false_type; using T = std::true_type;
#define PH(n) std::integral_constant<int, n>{}
    if (wg == 1) bar_arrive(1);
    mbar_wait(bar_full1 + 8 * s, ph);
    if (threadIdx.x == 0) TS(1);

    constexpr int sc1[11] = {0, XK, MH, XV, ML, RK | QK, S1, S2, RV | PV, ST0, ST1};
    constexpr int sc2[7] = {0, XK | MH, XV, ML, RK | QK, S1 | S2 | RV | PV, ST0 | ST1};
#define KSTEP(g2, sc, i, first, at, ta, next) \
    kstep(g2, PH(sc[i] & (QK | PV)), PH(sc[i + 1] & ~(QK | PV)), PH(sc[i + 1] & (QK | PV)), first, at, ta, true, next)
#pragma unroll 1
    for (int t = 0; t < 4; t++) {
      const bool at = t > 0;
      KSTEP(F{}, sc1, 0, true, at, t - 1, 0);  KSTEP(F{}, sc1, 1, false, at, t - 1, 0); KSTEP(F{}, sc1, 2, false, at, t - 1, 0);
      KSTEP(F{}, sc1, 3, false, at, t - 1, 0); KSTEP(F{}, sc1, 4, false, at, t - 1, 0); KSTEP(F{}, sc1, 5, false, at, t - 1, 0);
      KSTEP(F{}, sc1, 6, false, at, t - 1, 0); KSTEP(F{}, sc1, 7, false, at, t - 1, 0); KSTEP(F{}, sc1, 8, false, at, t - 1, 0);
      KSTEP(F{}, sc1, 9, false, at, t - 1, 0);
      if (threadIdx.x == 0) TS(3 + 2 * t);
#pragma unroll 1
      for (int ks = 10; ks < 16; ks++) kstep(F{}, PH(0), PH(0), PH(0), false, false, 0, true, t == 3 && ks == 15);
      fence_acc<0, 96>(acc);
#pragma unroll
      for (int i = 0; i < 48; i++) pk[i] = pack_bf16(acc[2 * i], acc[2 * i + 1]);
      if (threadIdx.x == 0) TS(2 + 2 * t);
    }
    KSTEP(T{}, sc2, 0, true, true, 3, 1);  KSTEP(T{}, sc2, 1, false, true, 3, 1); KSTEP(T{}, sc2, 2, false, true, 3, 1);
    KSTEP(T{}, sc2, 3, false, true, 3, 1); KSTEP(T{}, sc2, 4, false, true, 3, 1); KSTEP(T{}, sc2, 5, false, true, 3, 1);
    if (threadIdx.x == 0) TS(12);
#pragma unroll 1
    for (int ks = 6; ks < 12; ks++) kstep(T{}, PH(0), PH(0), PH(0), false, false, 0, true, 1);
    if (threadIdx.x == 0) TS(28);
    if (rel) mbar_arrive_cluster(rel);
    auto store_chunk = [&](auto chunk, float (&ac)[128]) __attribute__((always_inline)) {
      constexpr int c = decltype(chunk)::value;
      const uint32_t stg = (wg == 1 && c < 2) ? sb + OFF_X + (warp & 3) * 4096 + c * 2048 : sb + c * G2_STAGE + warp * 2048;
      const int r = ((lane >> 3) & 1) * 8 + (lane & 7);
#pragma unroll
      for (int jj = 0; jj < 8; jj += 2) {
        const int j = c * 8 + jj;
        stsm_x4(stg + r * 128 + (((jj + (lane >> 4)) ^ (r & 7)) << 4), pack_bf16(ac[4 * j], ac[4 * j + 1]),
                pack_bf16(ac[4 * j + 2], ac[4 * j + 3]), pack_bf16(ac[4 * j + 4], ac[4 * j + 5]),
                pack_bf16(ac[4 * j + 6], ac[4 * j + 7]));
      }
      fence_async_smem();
      __syncwarp();
      if (lane == 0) {
        tma_store_2d(&tm.out, e * 2048 + br * 1024 + cg * 256 + c * 64, rb * 128 + warp * 16, stg);
        bulk_commit();
      }
    };
    bar_sync(1 + wg);
    if (wg == 0) {
#pragma unroll 1
      for (int j = 0; j < 4; j++) {
        mbar_wait(bar_full2 + 8 * j, 1);
        const uint64_t da = desc_kmajor(sb + j * G2_STAGE);
        const uint64_t db = desc_mnmajor(sb + j * G2_STAGE + A_BYTES);
        wgmma_fence();
        wgmma_n256(acc2, da, db, 1);
        wgmma_n256(acc2, da + 2, db + 128, 1);
        wgmma_n256(acc2, da + 4, db + 1024, 1);
        wgmma_n256(acc2, da + 6, db + 1024 + 128, 1);
        wgmma_commit();
      }
      bar_arrive(2);
      wgmma_wait<0>();
      fence_acc<0, 128>(acc2);
      if (threadIdx.x == 0) TS(10);
      store_chunk(PH(0), acc2); store_chunk(PH(1), acc2); store_chunk(PH(2), acc2); store_chunk(PH(3), acc2);
    } else {
      float acc3[128];
#pragma unroll
      for (int i = 0; i < 128; i++) asm volatile("mov.b32 %0, %1;" : "=f"(acc3[i]) : "f"(acc2[i]));
      auto half_step = [&](auto side, int j) __attribute__((always_inline)) {
        constexpr int R = decltype(side)::value;
        const uint64_t da = desc_kmajor(sb + j * G2_STAGE + 8192);
        const uint64_t db = desc_mnmajor(sb + j * G2_STAGE + A_BYTES) + R * 512;
        wgmma_n128<R * 64>(acc3, da, db, 1);
        wgmma_n128<R * 64>(acc3, da + 2, db + 128, 1);
        wgmma_n128<R * 64>(acc3, da + 4, db + 1024, 1);
        wgmma_n128<R * 64>(acc3, da + 6, db + 1024 + 128, 1);
      };
#pragma unroll 1
      for (int j = 0; j < 4; j++) { mbar_wait(bar_full2 + 8 * j, 1); wgmma_fence(); half_step(PH(0), j); wgmma_commit(); }
      wgmma_fence();
#pragma unroll
      for (int j = 0; j < 4; j++) half_step(PH(1), j);
      wgmma_commit();
      wgmma_wait<1>();
      fence_acc<0, 64>(acc3);
      store_chunk(PH(0), acc3); store_chunk(PH(1), acc3);
      wgmma_wait<0>();
      fence_acc<64, 128>(acc3);
      if (threadIdx.x == 128) TS(29);
      store_chunk(PH(2), acc3); store_chunk(PH(3), acc3);
    }
    if (lane == 0) bulk_wait0_read();
    if (threadIdx.x == 0) { atomicAdd(&g_epoch[cta], 1u); TS(11); }
    if (threadIdx.x == 128) TS(13);
  } else {
    asm volatile("setmaxnreg.dec.sync.aligned.u32 40;");
    if (warp == 8 && lane == 0) {
      fence_async_smem();
      TS(14);
      for (int it = 0; it < G1_STAGES; it++) {
        const int s = (it + 1) % G1_STAGES;
        const uint32_t st = sb + s * G1_STAGE, fb = bar_full1 + 8 * s;
        if (START_DELAY > 0 && it >= START_AT) { const long long c0 = clock64(); while (clock64() - c0 < START_DELAY) {} }
        if (START_DELAY < 0 && it == START_AT) mbar_wait(bar_full1 + 8, 0);
        mbar_expect_tx(fb, G1_STAGE);
        tma_load_2d(st, it < START_P ? &tm.x0[br] : &tm.x[br], e * 1024 + it * 64, rb * 128, fb);
        tma_load_3d(st + A_BYTES, it < START_PW ? &tm.w0[br] : &tm.w[br], cg * 256, it * 64, 0, fb);
        tma_load_3d(st + A_BYTES + 12288, it < START_PW ? &tm.w0[br] : &tm.w[br], cg * 256, it * 64 + 32, 0, fb);
      }
    }
    __syncwarp();
    asm volatile("barrier.cluster.wait.aligned;" ::: "memory");
    if (warp == 8) {
      if (lane == 0) {
        int s = 1, ph = 0;
        TS(15);
        for (int it = G1_STAGES; it < 64; it++) {
          const int ks = it & 15, hp = cg * 4 + (it >> 4);
          const uint32_t st = sb + s * G1_STAGE, fb = bar_full1 + 8 * s;
          mbar_wait(bar_empty1 + 8 * s, ph);
          mbar_expect_tx(fb, G1_STAGE);
          tma_load_2d(st, &tm.x[br], e * 1024 + ks * 64, rb * 128, fb);
          tma_load_3d_mc(st + A_BYTES + e * 12288, &tm.w[br], hp * 64, ks * 64 + e * 32, 0, fb, (uint16_t)3);
          if (it == 8) { prefetch_tmap(&tm.wo[br]); prefetch_tmap(&tm.out); }
          if (++s == G1_STAGES) s = 0;
          if (s == 1) ph ^= 1;
        }
        for (int it = 0; it < 16; it++) {
          const int kb = (it & 3) * 4 + (it >> 2), s2 = it & 3;
          const uint32_t st = sb + s2 * G2_STAGE, fb = bar_full2 + 8 * s2;
          if (it < G2_STAGES) {
            if (it == 0) mbar_wait(bar_empty1, 1);
            mbar_wait(bar_empty1 + 8 * (it + 1), 0);
          } else {
            mbar_wait(bar_empty2 + 8 * s2, ((it >> 2) - 1) & 1);
          }
          mbar_expect_tx(fb, G2_STAGE);
          tma_load_3d_mc(st + A_BYTES + e * 16384, &tm.wo[br], 0, kb * 64 + e * 32, cg * 4, fb, (uint16_t)3);
          if ((it & 3) == 0) mbar_wait(bar_o + 8 * (it >> 2), 0);
          bulk_load(st, g_o + (((br * 8 + rb) * 2 + e) * 16 + kb) * 1024, A_BYTES, fb);
        }
      }
    } else {
      const unsigned tag = __ldcg(&g_epoch[cta]) + 1u;
      if (warp < 11) {
        const int half = warp - 9;
        ulonglong2* dst = g_halo + (cta + 8) * 4 * 256 + half * 128 + lane;
        const ulonglong2* src = g_halo + cta * 4 * 256 + half * 128 + lane;
        if (rb < 7) {
          mbar_wait(bar_empty1 + 32, 0);
          const unsigned long long inv = (unsigned long long)(tag - 1u) << 32;
#pragma unroll 1
          for (int t = 0; t < 4; t++) {
#pragma unroll
            for (int p = 0; p < 4; p++)
              asm volatile("st.relaxed.gpu.global.v2.b64 [%0], {%1, %1};" ::"l"(dst + t * 256 + p * 32), "l"(inv) : "memory");
            __nanosleep(500);
          }
        }
#pragma unroll 1
        for (int t = 0; t < 4; t++) {
          mbar_wait(bar_x + 128 + 8 * half, t & 1);
          if (rb < 7) {
            const unsigned long long hi = (unsigned long long)tag << 32;
#pragma unroll
            for (int i = 0; i < 2; i++) {
              const uint4 v = lds128(sb + OFF_X + 8 * 2048 + half * 1024 + i * 512 + lane * 16);
              asm volatile("st.relaxed.gpu.global.v2.b64 [%0], {%1, %2};" ::"l"(dst + t * 256 + i * 64), "l"(hi | v.x), "l"(hi | v.y) : "memory");
              asm volatile("st.relaxed.gpu.global.v2.b64 [%0], {%1, %2};" ::"l"(dst + t * 256 + i * 64 + 32), "l"(hi | v.z), "l"(hi | v.w) : "memory");
            }
          }
          __syncwarp();
          if (lane == 0) mbar_arrive(bar_o_empty);
          unsigned long long v[8];
          if (rb > 0) {
            uint32_t spins = 0;
            while (true) {
#pragma unroll
              for (int p = 0; p < 4; p++)
                asm volatile("ld.relaxed.gpu.global.v2.b64 {%0, %1}, [%2];" : "=l"(v[2 * p]), "=l"(v[2 * p + 1])
                             : "l"(src + t * 256 + p * 32) : "memory");
              bool ok = true;
#pragma unroll
              for (int p = 0; p < 8; p++) ok &= (unsigned)(v[p] >> 32) == tag;
              if (__all_sync(0xffffffffu, ok)) break;
              if (++spins > SPIN_LIMIT) __trap();
            }
          } else {
#pragma unroll
            for (int p = 0; p < 8; p++) v[p] = 0;
          }
#pragma unroll
          for (int i = 0; i < 2; i++)
            sts128(sb + OFF_X + half * 1024 + i * 512 + lane * 16, (uint32_t)v[4 * i], (uint32_t)v[4 * i + 1], (uint32_t)v[4 * i + 2], (uint32_t)v[4 * i + 3]);
          __syncwarp();
          if (lane == 0) { mbar_arrive(bar_x + 8 * half); if (t == 3) TS(30 + half); }
        }
      } else if (lane == 0) {
#pragma unroll 1
        for (int t = 0; t < 4; t++) {
          mbar_wait(bar_o_full, t & 1);
          TS(16 + t);
          unsigned* flag = &g_o_ready[((br * 8 + rb) * 2 + e) * 4 + t];
          for (int i = 0; i < 8; i++) {
            bulk_store(g_o + (((br * 8 + rb) * 2 + e) * 16 + cg * 4 + t) * 1024 + i * (1024 / 8), sb + OFF_X + i * (A_BYTES / 8), A_BYTES / 8);
            if (i + 1 < 8) __nanosleep(t < 3 ? O_SLEEP : O_SLEEP3);
          }
          bulk_commit();
          bulk_wait0_read();
          mbar_arrive(bar_o_empty);
          bulk_wait0();
          asm volatile("red.release.gpu.global.add.u32 [%0], 1;" ::"l"(flag) : "memory");
          TS(20 + t);
          wait_flag(flag, tag * 4u);
          asm volatile("fence.proxy.async.global;" ::: "memory");
          mbar_arrive(bar_o + 8 * t);
          TS(24 + t);
        }
      }
    }
  }
}

typedef CUresult (*EncodeFn)(CUtensorMap*, CUtensorMapDataType, cuuint32_t, void*, const cuuint64_t*, const cuuint64_t*,
                             const cuuint32_t*, const cuuint32_t*, CUtensorMapInterleave, CUtensorMapSwizzle,
                             CUtensorMapL2promotion, CUtensorMapFloatOOBfill);

bool encode(EncodeFn fn, CUtensorMap* m, const void* ptr, int rank, const cuuint64_t* dims, const cuuint64_t* strides,
            const cuuint32_t* box, CUtensorMapL2promotion promo = CU_TENSOR_MAP_L2_PROMOTION_L2_256B) {
  const cuuint32_t es[3] = {1, 1, 1};
  return fn(m, CU_TENSOR_MAP_DATA_TYPE_BFLOAT16, rank, const_cast<void*>(ptr), dims, strides, box, es,
            CU_TENSOR_MAP_INTERLEAVE_NONE, CU_TENSOR_MAP_SWIZZLE_128B, promo,
            CU_TENSOR_MAP_FLOAT_OOB_FILL_NONE) == CUDA_SUCCESS;
}

}

extern "C" void kernel_launch(void* const* d_in, const int* in_sizes, int n_in, void* d_out, int out_size) {
  (void)in_sizes; (void)n_in; (void)out_size;
  void* fp = nullptr;
  cudaDriverEntryPointQueryResult qr;
  if (cudaGetDriverEntryPoint("cuTensorMapEncodeTiled", &fp, cudaEnableDefault, &qr) != cudaSuccess || !fp) return;
  EncodeFn fn = (EncodeFn)fp;
  TMaps tm;
  bool ok = true;
  for (int b = 0; b < 2; b++) {
    tm.xp[b] = d_in[3 * b]; tm.wp[b] = d_in[3 * b + 1];
    {
      const cuuint64_t dims[2] = {2048, 1024}, str[1] = {4096};
      const cuuint32_t box[2] = {64, 128};
      ok &= encode(fn, &tm.x[b], d_in[3 * b + 0], 2, dims, str, box);
      ok &= encode(fn, &tm.x0[b], d_in[3 * b + 0], 2, dims, str, box, CU_TENSOR_MAP_L2_PROMOTION_L2_128B);
    }
    {
      const cuuint64_t dims[3] = {1024, 1024, 3}, str[2] = {6144, 2048};
      const cuuint32_t box[3] = {64, 32, 3};
      ok &= encode(fn, &tm.w[b], d_in[3 * b + 1], 3, dims, str, box);
      ok &= encode(fn, &tm.w0[b], d_in[3 * b + 1], 3, dims, str, box, CU_TENSOR_MAP_L2_PROMOTION_L2_128B);
    }
    {
      const cuuint64_t dims[3] = {64, 1024, 16}, str[2] = {2048, 128};
      const cuuint32_t box[3] = {64, 32, 4};
      ok &= encode(fn, &tm.wo[b], d_in[3 * b + 2], 3, dims, str, box);
    }
  }
  {
    const cuuint64_t dims[2] = {4096, 1024}, str[1] = {8192};
    const cuuint32_t box[2] = {64, 16};
    ok &= encode(fn, &tm.out, d_out, 2, dims, str, box);
  }
  if (!ok) return;
  cudaFuncSetAttribute(fused_kernel, cudaFuncAttributeMaxDynamicSharedMemorySize, SMEM_BYTES);
  fused_kernel<<<NUM_CTAS, NUM_THREADS, SMEM_BYTES>>>(tm);
}
```

```cpp
#include <cuda_runtime.h>
#include <cuda_bf16.h>
#include <cuda.h>
#include <stdint.h>
#include <type_traits>

namespace {

__device__ __forceinline__ void wgmma_n192(float (&d)[128], uint64_t da, uint64_t db, int scale_d) {
  asm volatile("{\n.reg .pred p;\nsetp.ne.b32 p, %98, 0;\n"
    "wgmma.mma_async.sync.aligned.m64n192k16.f32.bf16.bf16 "
    "{%0, %1, %2, %3, %4, %5, %6, %7, %8, %9, %10, %11, %12, %13, %14, %15, "
    "%16, %17, %18, %19, %20, %21, %22, %23, %24, %25, %26, %27, %28, %29, %30, %31, "
    "%32, %33, %34, %35, %36, %37, %38, %39, %40, %41, %42, %43, %44, %45, %46, %47, "
    "%48, %49, %50, %51, %52, %53, %54, %55, %56, %57, %58, %59, %60, %61, %62, %63, "
    "%64, %65, %66, %67, %68, %69, %70, %71, %72, %73, %74, %75, %76, %77, %78, %79, "
    "%80, %81, %82, %83, %84, %85, %86, %87, %88, %89, %90, %91, %92, %93, %94, %95}, "
    "%96, %97, p, 1, 1, 0, 1;\n}\n"
    : "+f"(d[0]), "+f"(d[1]), "+f"(d[2]), "+f"(d[3]), "+f"(d[4]), "+f"(d[5]), "+f"(d[6]), "+f"(d[7]),
      "+f"(d[8]), "+f"(d[9]), "+f"(d[10]), "+f"(d[11]), "+f"(d[12]), "+f"(d[13]), "+f"(d[14]), "+f"(d[15]),
      "+f"(d[16]), "+f"(d[17]), "+f"(d[18]), "+f"(d[19]), "+f"(d[20]), "+f"(d[21]), "+f"(d[22]), "+f"(d[23]),
      "+f"(d[24]), "+f"(d[25]), "+f"(d[26]), "+f"(d[27]), "+f"(d[28]), "+f"(d[29]), "+f"(d[30]), "+f"(d[31]),
      "+f"(d[32]), "+f"(d[33]), "+f"(d[34]), "+f"(d[35]), "+f"(d[36]), "+f"(d[37]), "+f"(d[38]), "+f"(d[39]),
      "+f"(d[40]), "+f"(d[41]), "+f"(d[42]), "+f"(d[43]), "+f"(d[44]), "+f"(d[45]), "+f"(d[46]), "+f"(d[47]),
      "+f"(d[48]), "+f"(d[49]), "+f"(d[50]), "+f"(d[51]), "+f"(d[52]), "+f"(d[53]), "+f"(d[54]), "+f"(d[55]),
      "+f"(d[56]), "+f"(d[57]), "+f"(d[58]), "+f"(d[59]), "+f"(d[60]), "+f"(d[61]), "+f"(d[62]), "+f"(d[63]),
      "+f"(d[64]), "+f"(d[65]), "+f"(d[66]), "+f"(d[67]), "+f"(d[68]), "+f"(d[69]), "+f"(d[70]), "+f"(d[71]),
      "+f"(d[72]), "+f"(d[73]), "+f"(d[74]), "+f"(d[75]), "+f"(d[76]), "+f"(d[77]), "+f"(d[78]), "+f"(d[79]),
      "+f"(d[80]), "+f"(d[81]), "+f"(d[82]), "+f"(d[83]), "+f"(d[84]), "+f"(d[85]), "+f"(d[86]), "+f"(d[87]),
      "+f"(d[88]), "+f"(d[89]), "+f"(d[90]), "+f"(d[91]), "+f"(d[92]), "+f"(d[93]), "+f"(d[94]), "+f"(d[95])
    : "l"(da), "l"(db), "r"(scale_d));
}

__device__ __forceinline__ void wgmma_n256(float (&d)[128], uint64_t da, uint64_t db, int scale_d) {
  asm volatile("{\n.reg .pred p;\nsetp.ne.b32 p, %130, 0;\n"
    "wgmma.mma_async.sync.aligned.m64n256k16.f32.bf16.bf16 "
    "{%0, %1, %2, %3, %4, %5, %6, %7, %8, %9, %10, %11, %12, %13, %14, %15, "
    "%16, %17, %18, %19, %20, %21, %22, %23, %24, %25, %26, %27, %28, %29, %30, %31, "
    "%32, %33, %34, %35, %36, %37, %38, %39, %40, %41, %42, %43, %44, %45, %46, %47, "
    "%48, %49, %50, %51, %52, %53, %54, %55, %56, %57, %58, %59, %60, %61, %62, %63, "
    "%64, %65, %66, %67, %68, %69, %70, %71, %72, %73, %74, %75, %76, %77, %78, %79, "
    "%80, %81, %82, %83, %84, %85, %86, %87, %88, %89, %90, %91, %92, %93, %94, %95, "
    "%96, %97, %98, %99, %100, %101, %102, %103, %104, %105, %106, %107, %108, %109, %110, %111, "
    "%112, %113, %114, %115, %116, %117, %118, %119, %120, %121, %122, %123, %124, %125, %126, %127}, "
    "%128, %129, p, 1, 1, 0, 1;\n}\n"
    : "+f"(d[0]), "+f"(d[1]), "+f"(d[2]), "+f"(d[3]), "+f"(d[4]), "+f"(d[5]), "+f"(d[6]), "+f"(d[7]),
      "+f"(d[8]), "+f"(d[9]), "+f"(d[10]), "+f"(d[11]), "+f"(d[12]), "+f"(d[13]), "+f"(d[14]), "+f"(d[15]),
      "+f"(d[16]), "+f"(d[17]), "+f"(d[18]), "+f"(d[19]), "+f"(d[20]), "+f"(d[21]), "+f"(d[22]), "+f"(d[23]),
      "+f"(d[24]), "+f"(d[25]), "+f"(d[26]), "+f"(d[27]), "+f"(d[28]), "+f"(d[29]), "+f"(d[30]), "+f"(d[31]),
      "+f"(d[32]), "+f"(d[33]), "+f"(d[34]), "+f"(d[35]), "+f"(d[36]), "+f"(d[37]), "+f"(d[38]), "+f"(d[39]),
      "+f"(d[40]), "+f"(d[41]), "+f"(d[42]), "+f"(d[43]), "+f"(d[44]), "+f"(d[45]), "+f"(d[46]), "+f"(d[47]),
      "+f"(d[48]), "+f"(d[49]), "+f"(d[50]), "+f"(d[51]), "+f"(d[52]), "+f"(d[53]), "+f"(d[54]), "+f"(d[55]),
      "+f"(d[56]), "+f"(d[57]), "+f"(d[58]), "+f"(d[59]), "+f"(d[60]), "+f"(d[61]), "+f"(d[62]), "+f"(d[63]),
      "+f"(d[64]), "+f"(d[65]), "+f"(d[66]), "+f"(d[67]), "+f"(d[68]), "+f"(d[69]), "+f"(d[70]), "+f"(d[71]),
      "+f"(d[72]), "+f"(d[73]), "+f"(d[74]), "+f"(d[75]), "+f"(d[76]), "+f"(d[77]), "+f"(d[78]), "+f"(d[79]),
      "+f"(d[80]), "+f"(d[81]), "+f"(d[82]), "+f"(d[83]), "+f"(d[84]), "+f"(d[85]), "+f"(d[86]), "+f"(d[87]),
      "+f"(d[88]), "+f"(d[89]), "+f"(d[90]), "+f"(d[91]), "+f"(d[92]), "+f"(d[93]), "+f"(d[94]), "+f"(d[95]),
      "+f"(d[96]), "+f"(d[97]), "+f"(d[98]), "+f"(d[99]), "+f"(d[100]), "+f"(d[101]), "+f"(d[102]), "+f"(d[103]),
      "+f"(d[104]), "+f"(d[105]), "+f"(d[106]), "+f"(d[107]), "+f"(d[108]), "+f"(d[109]), "+f"(d[110]), "+f"(d[111]),
      "+f"(d[112]), "+f"(d[113]), "+f"(d[114]), "+f"(d[115]), "+f"(d[116]), "+f"(d[117]), "+f"(d[118]), "+f"(d[119]),
      "+f"(d[120]), "+f"(d[121]), "+f"(d[122]), "+f"(d[123]), "+f"(d[124]), "+f"(d[125]), "+f"(d[126]), "+f"(d[127])
    : "l"(da), "l"(db), "r"(scale_d));
}

template <int O>
__device__ __forceinline__ void wgmma_n128(float (&d)[128], uint64_t da, uint64_t db, int scale_d) {
  asm volatile("{\n.reg .pred p;\nsetp.ne.b32 p, %66, 0;\n"
    "wgmma.mma_async.sync.aligned.m64n128k16.f32.bf16.bf16 "
    "{%0, %1, %2, %3, %4, %5, %6, %7, %8, %9, %10, %11, %12, %13, %14, %15, "
    "%16, %17, %18, %19, %20, %21, %22, %23, %24, %25, %26, %27, %28, %29, %30, %31, "
    "%32, %33, %34, %35, %36, %37, %38, %39, %40, %41, %42, %43, %44, %45, %46, %47, "
    "%48, %49, %50, %51, %52, %53, %54, %55, %56, %57, %58, %59, %60, %61, %62, %63}, "
    "%64, %65, p, 1, 1, 0, 1;\n}\n"
    : "+f"(d[O + 0]), "+f"(d[O + 1]), "+f"(d[O + 2]), "+f"(d[O + 3]), "+f"(d[O + 4]), "+f"(d[O + 5]), "+f"(d[O + 6]), "+f"(d[O + 7]),
      "+f"(d[O + 8]), "+f"(d[O + 9]), "+f"(d[O + 10]), "+f"(d[O + 11]), "+f"(d[O + 12]), "+f"(d[O + 13]), "+f"(d[O + 14]), "+f"(d[O + 15]),
      "+f"(d[O + 16]), "+f"(d[O + 17]), "+f"(d[O + 18]), "+f"(d[O + 19]), "+f"(d[O + 20]), "+f"(d[O + 21]), "+f"(d[O + 22]), "+f"(d[O + 23]),
      "+f"(d[O + 24]), "+f"(d[O + 25]), "+f"(d[O + 26]), "+f"(d[O + 27]), "+f"(d[O + 28]), "+f"(d[O + 29]), "+f"(d[O + 30]), "+f"(d[O + 31]),
      "+f"(d[O + 32]), "+f"(d[O + 33]), "+f"(d[O + 34]), "+f"(d[O + 35]), "+f"(d[O + 36]), "+f"(d[O + 37]), "+f"(d[O + 38]), "+f"(d[O + 39]),
      "+f"(d[O + 40]), "+f"(d[O + 41]), "+f"(d[O + 42]), "+f"(d[O + 43]), "+f"(d[O + 44]), "+f"(d[O + 45]), "+f"(d[O + 46]), "+f"(d[O + 47]),
      "+f"(d[O + 48]), "+f"(d[O + 49]), "+f"(d[O + 50]), "+f"(d[O + 51]), "+f"(d[O + 52]), "+f"(d[O + 53]), "+f"(d[O + 54]), "+f"(d[O + 55]),
      "+f"(d[O + 56]), "+f"(d[O + 57]), "+f"(d[O + 58]), "+f"(d[O + 59]), "+f"(d[O + 60]), "+f"(d[O + 61]), "+f"(d[O + 62]), "+f"(d[O + 63])
    : "l"(da), "l"(db), "r"(scale_d));
}

constexpr int NUM_CTAS = 128;
constexpr int NUM_THREADS = 384;
constexpr int G1_STAGES = 5, G2_STAGES = 4;
constexpr uint32_t A_BYTES = 16384;
constexpr uint32_t G1_STAGE = 40960;
constexpr uint32_t G2_STAGE = 49152;
constexpr uint32_t RING_BYTES = G1_STAGES * G1_STAGE;
constexpr uint32_t OFF_X = RING_BYTES;
constexpr uint32_t OFF_BAR = OFF_X + 9 * 2048;
constexpr uint32_t SMEM_BYTES = OFF_BAR + 512;
constexpr uint32_t SPIN_LIMIT = 1u << 21;

struct alignas(64) TMaps {
  CUtensorMap x[2], w[2], wo[2], out;
  CUtensorMap x0[2], w0[2];
  const void* xp[2];
  const void* wp[2];
  uint32_t zero;
};

__device__ uint4 g_o[32 * 16 * 1024];
__device__ ulonglong2 g_halo[NUM_CTAS * 4 * 256];
__device__ unsigned g_o_ready[32 * 4];
__device__ unsigned g_epoch[NUM_CTAS];
#define TS(slot)
#define KS(i)

__device__ __forceinline__ void mbar_init(uint32_t bar, uint32_t count) {
  asm volatile("mbarrier.init.shared::cta.b64 [%0], %1;" ::"r"(bar), "r"(count) : "memory");
}
__device__ __forceinline__ bool mbar_try_wait(uint32_t bar, uint32_t parity) {
  uint32_t ok;
  asm volatile("{\n.reg .pred p;\nmbarrier.try_wait.parity.shared::cta.b64 p, [%1], %2;\nselp.u32 %0, 1, 0, p;\n}\n"
               : "=r"(ok) : "r"(bar), "r"(parity) : "memory");
  return ok != 0;
}
__device__ __forceinline__ void mbar_wait(uint32_t bar, uint32_t parity) {
  uint32_t spins = 0;
  while (!mbar_try_wait(bar, parity)) { if (++spins > SPIN_LIMIT) __trap(); }
}
__device__ __forceinline__ void mbar_arrive(uint32_t bar) {
  asm volatile("mbarrier.arrive.shared::cta.b64 _, [%0];" ::"r"(bar) : "memory");
}
__device__ __forceinline__ void mbar_arrive_cluster(uint32_t bar_cluster_addr) {
  asm volatile("mbarrier.arrive.shared::cluster.b64 _, [%0];" ::"r"(bar_cluster_addr) : "memory");
}
__device__ __forceinline__ void mbar_expect_tx(uint32_t bar, uint32_t bytes) {
  asm volatile("mbarrier.arrive.expect_tx.shared::cta.b64 _, [%0], %1;" ::"r"(bar), "r"(bytes) : "memory");
}
__device__ __forceinline__ uint32_t mapa(uint32_t addr, uint32_t rank) {
  uint32_t r; asm("mapa.shared::cluster.u32 %0, %1, %2;" : "=r"(r) : "r"(addr), "r"(rank)); return r;
}
__device__ __forceinline__ void tma_load_2d(uint32_t dst, const CUtensorMap* m, int c0, int c1, uint32_t bar) {
  asm volatile("cp.async.bulk.tensor.2d.shared::cluster.global.mbarrier::complete_tx::bytes [%0], [%1, {%3, %4}], [%2];"
               ::"r"(dst), "l"(m), "r"(bar), "r"(c0), "r"(c1) : "memory");
}
__device__ __forceinline__ void tma_load_3d(uint32_t dst, const CUtensorMap* m, int c0, int c1, int c2, uint32_t bar) {
  asm volatile("cp.async.bulk.tensor.3d.shared::cluster.global.mbarrier::complete_tx::bytes [%0], [%1, {%3, %4, %5}], [%2];"
               ::"r"(dst), "l"(m), "r"(bar), "r"(c0), "r"(c1), "r"(c2) : "memory");
}
__device__ __forceinline__ void tma_load_3d_mc(uint32_t dst, const CUtensorMap* m, int c0, int c1, int c2, uint32_t bar, uint16_t mask) {
  asm volatile("cp.async.bulk.tensor.3d.shared::cluster.global.mbarrier::complete_tx::bytes.multicast::cluster [%0], [%1, {%3, %4, %5}], [%2], %6;"
               ::"r"(dst), "l"(m), "r"(bar), "r"(c0), "r"(c1), "r"(c2), "h"(mask) : "memory");
}
__device__ __forceinline__ void tma_store_2d(const CUtensorMap* m, int c0, int c1, uint32_t src) {
  asm volatile("cp.async.bulk.tensor.2d.global.shared::cta.bulk_group [%0, {%2, %3}], [%1];"
               ::"l"(m), "r"(src), "r"(c0), "r"(c1) : "memory");
}
__device__ __forceinline__ void bulk_load(uint32_t dst, const void* src, uint32_t bytes, uint32_t bar) {
  asm volatile("cp.async.bulk.shared::cluster.global.mbarrier::complete_tx::bytes [%0], [%1], %2, [%3];"
               ::"r"(dst), "l"(src), "r"(bytes), "r"(bar) : "memory");
}
__device__ __forceinline__ void bulk_store(void* dst, uint32_t src, uint32_t bytes) {
  asm volatile("cp.async.bulk.global.shared::cta.bulk_group [%0], [%1], %2;" ::"l"(dst), "r"(src), "r"(bytes) : "memory");
}
__device__ __forceinline__ void bulk_commit() { asm volatile("cp.async.bulk.commit_group;" ::: "memory"); }
__device__ __forceinline__ void bulk_wait0() { asm volatile("cp.async.bulk.wait_group 0;" ::: "memory"); }
__device__ __forceinline__ void bulk_wait0_read() { asm volatile("cp.async.bulk.wait_group.read 0;" ::: "memory"); }
__device__ __forceinline__ void fence_async_smem() { asm volatile("fence.proxy.async.shared::cta;" ::: "memory"); }
__device__ __forceinline__ void prefetch_tmap(const CUtensorMap* m) {
  asm volatile("prefetch.tensormap [%0];" ::"l"(m) : "memory");
}
__device__ __forceinline__ void wgmma_fence() { asm volatile("wgmma.fence.sync.aligned;" ::: "memory"); }
__device__ __forceinline__ void wgmma_commit() { asm volatile("wgmma.commit_group.sync.aligned;" ::: "memory"); }
template <int N> __device__ __forceinline__ void wgmma_wait() { asm volatile("wgmma.wait_group.sync.aligned %0;" ::"n"(N) : "memory"); }
template <int B, int N> __device__ __forceinline__ void fence_acc(float (&d)[128]) {
#pragma unroll
  for (int i = B; i < N; i++) asm volatile("" : "+f"(d[i])::"memory");
}
__device__ __forceinline__ void bar_sync(int id) { asm volatile("bar.sync %0, 256;" ::"r"(id) : "memory"); }
__device__ __forceinline__ void bar_arrive(int id) { asm volatile("bar.arrive %0, 256;" ::"r"(id) : "memory"); }
__device__ __forceinline__ uint64_t desc_kmajor(uint32_t addr) {
  return (uint64_t)((addr & 0x3FFFF) >> 4) | (1ull << 16) | (64ull << 32) | (1ull << 62);
}
__device__ __forceinline__ uint64_t desc_mnmajor(uint32_t addr) {
  return (uint64_t)((addr & 0x3FFFF) >> 4) | (256ull << 16) | (64ull << 32) | (1ull << 62);
}
__device__ __forceinline__ uint32_t pack_bf16(float lo, float hi) {
  uint32_t r; asm("cvt.rn.bf16x2.f32 %0, %1, %2;" : "=r"(r) : "f"(hi), "f"(lo)); return r;
}
__device__ __forceinline__ void stsm_x4(uint32_t addr, uint32_t r0, uint32_t r1, uint32_t r2, uint32_t r3) {
  asm volatile("stmatrix.sync.aligned.m8n8.x4.shared.b16 [%0], {%1, %2, %3, %4};" ::"r"(addr), "r"(r0), "r"(r1), "r"(r2), "r"(r3) : "memory");
}
__device__ __forceinline__ void stsm_x4_t(uint32_t addr, uint32_t r0, uint32_t r1, uint32_t r2, uint32_t r3) {
  asm volatile("stmatrix.sync.aligned.m8n8.x4.trans.shared.b16 [%0], {%1, %2, %3, %4};" ::"r"(addr), "r"(r0), "r"(r1), "r"(r2), "r"(r3) : "memory");
}
__device__ __forceinline__ uint32_t movm_t(uint32_t a) {
  uint32_t d; asm volatile("movmatrix.sync.aligned.m8n8.trans.b16 %0, %1;" : "=r"(d) : "r"(a)); return d;
}
__device__ __forceinline__ void mma_init(float (&c)[4], uint32_t a0, uint32_t a1, uint32_t a2, uint32_t a3, uint32_t b0, uint32_t b1) {
  asm volatile("mma.sync.aligned.m16n8k16.row.col.f32.bf16.bf16.f32 {%0, %1, %2, %3}, {%4, %5, %6, %7}, {%8, %9}, {%10, %10, %10, %10};"
               : "=f"(c[0]), "=f"(c[1]), "=f"(c[2]), "=f"(c[3]) : "r"(a0), "r"(a1), "r"(a2), "r"(a3), "r"(b0), "r"(b1), "f"(0.f));
}
__device__ __forceinline__ void mma_acc(float (&c)[4], uint32_t a0, uint32_t a1, uint32_t a2, uint32_t a3, uint32_t b0, uint32_t b1) {
  asm volatile("mma.sync.aligned.m16n8k16.row.col.f32.bf16.bf16.f32 {%0, %1, %2, %3}, {%4, %5, %6, %7}, {%8, %9}, {%0, %1, %2, %3};"
               : "+f"(c[0]), "+f"(c[1]), "+f"(c[2]), "+f"(c[3]) : "r"(a0), "r"(a1), "r"(a2), "r"(a3), "r"(b0), "r"(b1));
}
__device__ __forceinline__ float ex2(float x) { float y; asm("ex2.approx.ftz.f32 %0, %1;" : "=f"(y) : "f"(x)); return y; }
__device__ __forceinline__ unsigned ld_acquire(const unsigned* p) {
  unsigned v; asm volatile("ld.acquire.gpu.global.u32 %0, [%1];" : "=r"(v) : "l"(p) : "memory"); return v;
}
__device__ __forceinline__ void wait_flag(const unsigned* p, unsigned target) {
  uint32_t spins = 0;
  while ((int)(ld_acquire(p) - target) < 0) { if (++spins > SPIN_LIMIT) __trap(); __nanosleep(20); }
}
__device__ __forceinline__ uint4 lds128(uint32_t addr) {
  uint4 v; asm volatile("ld.shared.v4.u32 {%0, %1, %2, %3}, [%4];" : "=r"(v.x), "=r"(v.y), "=r"(v.z), "=r"(v.w) : "r"(addr) : "memory"); return v;
}
__device__ __forceinline__ void sts128(uint32_t addr, uint32_t a, uint32_t b, uint32_t c, uint32_t d) {
  asm volatile("st.shared.v4.u32 [%0], {%1, %2, %3, %4};" ::"r"(addr), "r"(a), "r"(b), "r"(c), "r"(d) : "memory");
}

template <int N>
__device__ __forceinline__ void softmax_exp(const float (&lo)[N][2], const float (&hi)[N][2], bool use_lo0, bool use_lo1,
                                            float (&ex)[N][2]) {
  constexpr float kScale = 0.17677669529663687f, kLog2e = 1.4426950408889634f;
  float m[N];
#pragma unroll
  for (int i = 0; i < N; i++) {
    uint32_t p = pack_bf16(use_lo0 ? lo[i][0] : hi[i][0], use_lo1 ? lo[i][1] : hi[i][1]);
    p = pack_bf16(__uint_as_float(p << 16) * kScale, __uint_as_float(p & 0xffff0000u) * kScale);
    ex[i][0] = __uint_as_float(p << 16);
    ex[i][1] = __uint_as_float(p & 0xffff0000u);
    m[i] = fmaxf(ex[i][0], ex[i][1]);
  }
#pragma unroll
  for (int i = 0; i < N; i++) m[i] = fmaxf(m[i], __shfl_xor_sync(0xffffffffu, m[i], 1));
#pragma unroll
  for (int i = 0; i < N; i++) m[i] = fmaxf(m[i], __shfl_xor_sync(0xffffffffu, m[i], 2));
#pragma unroll
  for (int i = 0; i < N; i++) { ex[i][0] = ex2((ex[i][0] - m[i]) * kLog2e); ex[i][1] = ex2((ex[i][1] - m[i]) * kLog2e); }
}
template <int N>
__device__ __forceinline__ void softmax_norm(const float (&ex)[N][2], uint32_t lo_mask, uint32_t (&b_lo)[N], uint32_t (&b_hi)[N]) {
  float s[N];
#pragma unroll
  for (int i = 0; i < N; i++) s[i] = ex[i][0] + ex[i][1];
#pragma unroll
  for (int i = 0; i < N; i++) s[i] += __shfl_xor_sync(0xffffffffu, s[i], 1);
#pragma unroll
  for (int i = 0; i < N; i++) s[i] += __shfl_xor_sync(0xffffffffu, s[i], 2);
#pragma unroll
  for (int i = 0; i < N; i++) {
    float r;
    asm("rcp.approx.ftz.f32 %0, %1;" : "=f"(r) : "f"(s[i]));
    const uint32_t p = pack_bf16(ex[i][0] * r, ex[i][1] * r);
    b_lo[i] = p & lo_mask;
    b_hi[i] = p & ~lo_mask;
  }
}

__global__ void __cluster_dims__(2, 1, 1) __launch_bounds__(NUM_THREADS, 1)
fused_kernel(const __grid_constant__ TMaps tm) {
  extern __shared__ __align__(1024) uint8_t smem_raw[];
  const uint32_t sb = (uint32_t)__cvta_generic_to_shared(smem_raw);
  const int warp = __shfl_sync(0xffffffffu, threadIdx.x >> 5, 0), lane = threadIdx.x & 31;
  const int e = blockIdx.x & 1;
  int cg, rb, br;
  {
    const int c = blockIdx.x >> 1;
    int q, i;
    if (c < 4) { q = 0; i = c; }
    else if (c < 36) { q = 1 + ((c - 4) & 7); i = (c - 4) >> 3; }
    else { q = 9 + (c - 36) % 7; i = (c - 36) / 7; }
    cg = i; rb = q & 7; br = q >> 3;
  }
  const int cta = e + 2 * cg + 8 * rb + 64 * br;
  const uint32_t bar_full1 = sb + OFF_BAR, bar_empty1 = bar_full1 + 64, bar_full2 = bar_full1 + 128,
                 bar_empty2 = bar_full1 + 160, bar_o_full = bar_full1 + 192, bar_o_empty = bar_full1 + 200,
                 bar_o = bar_full1 + 208  , bar_x = bar_full1 + 240  ;

  if (threadIdx.x == 0) TS(0);
  if (warp == 8 && lane == 0) {
    prefetch_tmap(&tm.x0[br]); prefetch_tmap(&tm.w0[br]);
    prefetch_tmap(&tm.x[br]); prefetch_tmap(&tm.w[br]);
    for (int s = 0; s < G1_STAGES; s++) mbar_init(bar_full1 + 8 * s, 1);
    asm volatile("fence.mbarrier_init.release.cluster;" ::: "memory");
  } else if (warp == 9 && lane == 0) {
    for (int s = 0; s < G1_STAGES; s++) mbar_init(bar_empty1 + 8 * s, 16);
    for (int s = 0; s < G2_STAGES; s++) { mbar_init(bar_full2 + 8 * s, 1); mbar_init(bar_empty2 + 8 * s, 16); }
    for (int s = 0; s < 18; s++) mbar_init(bar_x + 8 * s, 1);
    mbar_init(bar_o_full, 8); mbar_init(bar_o_empty, 3);
    for (int t = 0; t < 4; t++) mbar_init(bar_o + 8 * t, 1);
    asm volatile("fence.mbarrier_init.release.cluster;" ::: "memory");
  } else if (warp < 2) {
    if (warp == 0) {
      const char* p = (const char*)tm.xp[br] + (size_t)(rb * 128 + cg * 32 + lane) * 4096 + e * 2048;
      asm volatile("prefetch.global.L2 [%0];" ::"l"(p));
    } else if (lane < 12) {
      const int l = rb * 2 + e + 16 * lane;
      const char* p = (const char*)tm.wp[br] + (size_t)(l / 3) * 6144 + (l % 3) * 2048 + cg * 512;
      asm volatile("prefetch.global.L2 [%0];" ::"l"(p));
    }
  }
  __syncwarp();
  asm volatile("barrier.cluster.arrive.relaxed.aligned;" ::: "memory");

  if (warp < 8) {
    asm volatile("setmaxnreg.inc.sync.aligned.u32 232;");
    asm volatile("barrier.cluster.wait.aligned;" ::: "memory");
    const int wg = warp >> 2;
    float acc[128], acc2[128];
    uint32_t pk[48];
    float of[8][4];
    uint32_t xp[8];
    float pe[4][2];
    uint32_t b_lo[4], b_hi[4];
    const bool rel_any = lane < 2;
    const uint32_t rel_base = mapa(bar_full1, lane == 0 ? e : (e ^ 1));
    const int g = lane >> 2, tq = lane & 3;
    const bool use_lo0 = (2 * tq) > g, use_lo1 = (2 * tq + 1) > g;
    const uint32_t lo_mask = (use_lo0 ? 0xffffu : 0u) | (use_lo1 ? 0xffff0000u : 0u);
    const bool seq_start = (rb == 0 && warp == 0);
    const uint32_t slot = sb + OFF_X + warp * 2048;
    int s = 1, ph = 0;
    int kcount = 0; (void)kcount; unsigned kc[4]; (void)kc;

    enum { XK = 1, MH = 2, XV = 4, ML = 8, RK = 16, S1 = 32, S2 = 64, RV = 128, ST0 = 256, ST1 = 512, QK = 1024, PV = 2048 };
    auto attn = [&](auto phase, int ta) __attribute__((always_inline)) {
      constexpr int P = decltype(phase)::value;
      if constexpr ((P & XK) != 0) {
        if (ta > 0) mbar_wait(bar_o_empty, (ta - 1) & 1);
        sts128(slot + 2048 + lane * 16, pk[17], pk[19], pk[21], pk[23]);
        sts128(slot + 2560 + lane * 16, pk[25], pk[27], pk[29], pk[31]);
        __syncwarp();
        if (lane == 0) mbar_arrive(bar_x + 16 * warp + 16);
      }
      if constexpr ((P & MH) != 0) {
#pragma unroll
        for (int i = 1; i < 16; i += 2) pk[32 + i] = movm_t(pk[32 + i]);
      }
      if constexpr ((P & XV) != 0) {
        sts128(slot + 3072 + lane * 16, pk[33], pk[35], pk[37], pk[39]);
        sts128(slot + 3584 + lane * 16, pk[41], pk[43], pk[45], pk[47]);
        __syncwarp();
        if (lane == 0) mbar_arrive(bar_x + 16 * warp + 24);
      }
      if constexpr ((P & ML) != 0) {
#pragma unroll
        for (int i = 0; i < 16; i += 2) pk[32 + i] = movm_t(pk[32 + i]);
      }
      if constexpr ((P & S1) != 0) {
        if (seq_start) of[0][0] = of[0][1] = of[3][0] = of[3][1] = -INFINITY;
        const float lo[4][2] = {{of[0][0], of[0][1]}, {of[1][2], of[1][3]}, {of[3][0], of[3][1]}, {of[4][2], of[4][3]}};
        const float hi[4][2] = {{of[1][0], of[1][1]}, {of[2][2], of[2][3]}, {of[4][0], of[4][1]}, {of[5][2], of[5][3]}};
        softmax_exp<4>(lo, hi, use_lo0, use_lo1, pe);
      }
      if constexpr ((P & S2) != 0) softmax_norm<4>(pe, lo_mask, b_lo, b_hi);
      if constexpr ((P & (RK | RV)) != 0) {
        constexpr int V = (P & RV) != 0;
        mbar_wait(bar_x + 16 * warp + 8 * V, ta & 1);
        const uint4 x0 = lds128(slot + V * 1024 + lane * 16), x1 = lds128(slot + V * 1024 + 512 + lane * 16);
        xp[0] = x0.x; xp[1] = x0.y; xp[2] = x0.z; xp[3] = x0.w; xp[4] = x1.x; xp[5] = x1.y; xp[6] = x1.z; xp[7] = x1.w;
      }
      if constexpr ((P & (ST0 | ST1)) != 0) {
#pragma unroll
        for (int i = (P & ST0) ? 0 : 2; i < ((P & ST1) ? 4 : 2); i++)
          stsm_x4_t(slot + ((i & 1) * 8 + (lane & 7)) * 128 + ((((i >> 1) * 4 + (lane >> 3)) ^ (lane & 7)) << 4),
                    pack_bf16(of[2 * i][0], of[2 * i][1]), pack_bf16(of[2 * i][2], of[2 * i][3]),
                    pack_bf16(of[2 * i + 1][0], of[2 * i + 1][1]), pack_bf16(of[2 * i + 1][2], of[2 * i + 1][3]));
        if constexpr ((P & ST1) != 0) {
          fence_async_smem();
          __syncwarp();
          if (lane == 0) mbar_arrive(bar_o_full);
        }
      }
    };
    auto burst = [&](auto phase, auto from, auto to) __attribute__((always_inline)) {
      constexpr int P = decltype(phase)::value, B = decltype(from)::value, E = decltype(to)::value;
#pragma unroll
      for (int n = B; n < E; n++) {
        if constexpr (P == QK) {
          const int k = n / 6, h = (n % 6) / 3, j = n % 3, q = 8 * h + 4 * k;
          const uint32_t b0 = j == 0 ? xp[4 * h + 2 * k] : pk[15 + q + j], b1 = j == 0 ? xp[4 * h + 2 * k + 1] : pk[17 + q + j];
          if (k == 0) mma_init(of[3 * h + j], pk[q], pk[q + 1], pk[q + 2], pk[q + 3], b0, b1);
          else mma_acc(of[3 * h + j], pk[q], pk[q + 1], pk[q + 2], pk[q + 3], b0, b1);
        } else {
          const int h = n / 4, hf = (n / 2) & 1, d = n & 1, v = 32 + 8 * h + 4 * d;
          if (hf == 0) mma_init(of[n], xp[4 * h + 2 * d], xp[4 * h + 2 * d + 1], pk[v], pk[v + 2], b_lo[2 * h], b_hi[2 * h]);
          else mma_init(of[n], pk[v], pk[v + 2], pk[v + 1], pk[v + 3], b_lo[2 * h + 1], b_hi[2 * h + 1]);
        }
      }
    };
#define PH(n) std::integral_constant<int, n>{}
    uint32_t rel = 0;
    auto kstep = [&](auto g2, auto pre0, auto post, auto burst1, bool first, bool do_attn, int ta, bool release, int next) __attribute__((always_inline)) {
      constexpr bool G2 = decltype(g2)::value;
      constexpr uint32_t STAGE = G2 ? G2_STAGE : G1_STAGE;
      constexpr uint64_t HALF = G2 ? 1024 : 768;
      const uint64_t da = desc_kmajor(sb + s * STAGE + wg * 8192);
      const uint64_t db = desc_mnmajor(sb + s * STAGE + A_BYTES);
      if constexpr (decltype(pre0)::value != 0) { if (do_attn && wg == 0) burst(pre0, PH(0), PH(decltype(pre0)::value == QK ? 12 : 8)); }
      bar_sync(1 + wg);
      KS(0);
      wgmma_fence();
      if constexpr (G2) {
        wgmma_n256(acc2, da, db, !first);
        wgmma_n256(acc2, da + 2, db + 128, 1);
        wgmma_n256(acc2, da + 4, db + HALF, 1);
        wgmma_n256(acc2, da + 6, db + HALF + 128, 1);
      } else {
        wgmma_n192(acc, da, db, !first);
        wgmma_n192(acc, da + 2, db + 128, 1);
        wgmma_n192(acc, da + 4, db + HALF, 1);
        wgmma_n192(acc, da + 6, db + HALF + 128, 1);
      }
      wgmma_commit();
      const bool late = decltype(burst1)::value != 0 && do_attn && wg == 1;
      if (!late && !(next < 0 && wg == 1)) bar_arrive(2 - wg);
      if (rel) mbar_arrive_cluster(rel);
      rel = (release && rel_any) ? rel_base + (G2 ? 160 : 64) + 8 * s : 0;
      KS(1);
      if constexpr (decltype(post)::value != 0) { if (do_attn) attn(post, ta); }
      if (++s == (G2 ? G2_STAGES : G1_STAGES)) s = 0;
      if (s == (G2 ? 0 : 1)) ph ^= 1;
      if (!G2 && next == 1) { s = 0; ph = 0; }
      if (next >= 0) mbar_wait((next ? bar_full2 : bar_full1) + 8 * s, ph);
      if constexpr (decltype(burst1)::value != 0) {
        if (late) {
          constexpr int N = decltype(burst1)::value == QK ? 12 : 8, M = decltype(burst1)::value == QK ? 7 : 5;
          burst(burst1, PH(0), PH(N - M));
          if (tm.zero) __trap();
          bar_arrive(1);
          burst(burst1, PH(N - M), PH(N));
        }
      }
      KS(2);
      wgmma_wait<0>();
      KS(3); kcount++;
    };
    using F = std::false_type; using T = std::true_type;
    if (wg == 1) bar_arrive(1);
    mbar_wait(bar_full1 + 8 * s, ph);
    if (threadIdx.x == 0) TS(1);

    constexpr int sc1[11] = {0, XK, MH, XV, ML, RK | QK, S1, S2, RV | PV, ST0, ST1};
    constexpr int sc2[7] = {0, XK | MH, XV, ML, RK | QK, S1 | S2 | RV | PV, ST0 | ST1};
#define KSTEP(g2, sc, i, first, at, ta, next) \
    kstep(g2, PH(sc[i] & (QK | PV)), PH(sc[i + 1] & ~(QK | PV)), PH(sc[i + 1] & (QK | PV)), first, at, ta, true, next)
#pragma unroll 1
    for (int t = 0; t < 4; t++) {
      const bool at = t > 0;
      KSTEP(F{}, sc1, 0, true, at, t - 1, 0);  KSTEP(F{}, sc1, 1, false, at, t - 1, 0); KSTEP(F{}, sc1, 2, false, at, t - 1, 0);
      KSTEP(F{}, sc1, 3, false, at, t - 1, 0); KSTEP(F{}, sc1, 4, false, at, t - 1, 0); KSTEP(F{}, sc1, 5, false, at, t - 1, 0);
      KSTEP(F{}, sc1, 6, false, at, t - 1, 0); KSTEP(F{}, sc1, 7, false, at, t - 1, 0); KSTEP(F{}, sc1, 8, false, at, t - 1, 0);
      KSTEP(F{}, sc1, 9, false, at, t - 1, 0);
      if (threadIdx.x == 0) TS(3 + 2 * t);
#pragma unroll 1
      for (int ks = 10; ks < 16; ks++) kstep(F{}, PH(0), PH(0), PH(0), false, false, 0, true, t == 3 && ks == 15);
      fence_acc<0, 96>(acc);
#pragma unroll
      for (int i = 0; i < 48; i++) pk[i] = pack_bf16(acc[2 * i], acc[2 * i + 1]);
      if (threadIdx.x == 0) TS(2 + 2 * t);
    }
    KSTEP(T{}, sc2, 0, true, true, 3, 1);  KSTEP(T{}, sc2, 1, false, true, 3, 1); KSTEP(T{}, sc2, 2, false, true, 3, 1);
    KSTEP(T{}, sc2, 3, false, true, 3, 1); KSTEP(T{}, sc2, 4, false, true, 3, 1); KSTEP(T{}, sc2, 5, false, true, 3, 1);
    if (threadIdx.x == 0) TS(12);
#pragma unroll 1
    for (int ks = 6; ks < 12; ks++) kstep(T{}, PH(0), PH(0), PH(0), false, false, 0, true, 1);
    if (threadIdx.x == 0) TS(28);
    if (rel) mbar_arrive_cluster(rel);
    auto store_chunk = [&](auto chunk, float (&ac)[128]) __attribute__((always_inline)) {
      constexpr int c = decltype(chunk)::value;
      const uint32_t stg = (wg == 1 && c < 2) ? sb + OFF_X + (warp & 3) * 4096 + c * 2048 : sb + c * G2_STAGE + warp * 2048;
      const int r = ((lane >> 3) & 1) * 8 + (lane & 7);
#pragma unroll
      for (int jj = 0; jj < 8; jj += 2) {
        const int j = c * 8 + jj;
        stsm_x4(stg + r * 128 + (((jj + (lane >> 4)) ^ (r & 7)) << 4), pack_bf16(ac[4 * j], ac[4 * j + 1]),
                pack_bf16(ac[4 * j + 2], ac[4 * j + 3]), pack_bf16(ac[4 * j + 4], ac[4 * j + 5]),
                pack_bf16(ac[4 * j + 6], ac[4 * j + 7]));
      }
      fence_async_smem();
      __syncwarp();
      if (lane == 0) {
        tma_store_2d(&tm.out, e * 2048 + br * 1024 + cg * 256 + c * 64, rb * 128 + warp * 16, stg);
        bulk_commit();
      }
    };
    bar_sync(1 + wg);
    if (wg == 0) {
#pragma unroll 1
      for (int j = 0; j < 4; j++) {
        mbar_wait(bar_full2 + 8 * j, 1);
        const uint64_t da = desc_kmajor(sb + j * G2_STAGE);
        const uint64_t db = desc_mnmajor(sb + j * G2_STAGE + A_BYTES);
        wgmma_fence();
        wgmma_n256(acc2, da, db, 1);
        wgmma_n256(acc2, da + 2, db + 128, 1);
        wgmma_n256(acc2, da + 4, db + 1024, 1);
        wgmma_n256(acc2, da + 6, db + 1024 + 128, 1);
        wgmma_commit();
      }
      bar_arrive(2);
      wgmma_wait<0>();
      fence_acc<0, 128>(acc2);
      if (threadIdx.x == 0) TS(10);
      store_chunk(PH(0), acc2); store_chunk(PH(1), acc2); store_chunk(PH(2), acc2); store_chunk(PH(3), acc2);
    } else {
      float acc3[128];
#pragma unroll
      for (int i = 0; i < 128; i++) asm volatile("mov.b32 %0, %1;" : "=f"(acc3[i]) : "f"(acc2[i]));
      auto half_step = [&](auto side, int j) __attribute__((always_inline)) {
        constexpr int R = decltype(side)::value;
        const uint64_t da = desc_kmajor(sb + j * G2_STAGE + 8192);
        const uint64_t db = desc_mnmajor(sb + j * G2_STAGE + A_BYTES) + R * 512;
        wgmma_n128<R * 64>(acc3, da, db, 1);
        wgmma_n128<R * 64>(acc3, da + 2, db + 128, 1);
        wgmma_n128<R * 64>(acc3, da + 4, db + 1024, 1);
        wgmma_n128<R * 64>(acc3, da + 6, db + 1024 + 128, 1);
      };
#pragma unroll 1
      for (int j = 0; j < 4; j++) { mbar_wait(bar_full2 + 8 * j, 1); wgmma_fence(); half_step(PH(0), j); wgmma_commit(); }
      wgmma_fence();
#pragma unroll
      for (int j = 0; j < 4; j++) half_step(PH(1), j);
      wgmma_commit();
      wgmma_wait<1>();
      fence_acc<0, 64>(acc3);
      store_chunk(PH(0), acc3); store_chunk(PH(1), acc3);
      wgmma_wait<0>();
      fence_acc<64, 128>(acc3);
      if (threadIdx.x == 128) TS(29);
      store_chunk(PH(2), acc3); store_chunk(PH(3), acc3);
    }
    if (lane == 0) bulk_wait0_read();
    if (threadIdx.x == 0) { atomicAdd(&g_epoch[cta], 1u); TS(11); }
    if (threadIdx.x == 128) TS(13);
  } else {
    asm volatile("setmaxnreg.dec.sync.aligned.u32 40;");
    if (warp == 8 && lane == 0) {
      fence_async_smem();
      TS(14);
      for (int it = 0; it < G1_STAGES; it++) {
        const int s = (it + 1) % G1_STAGES;
        const uint32_t st = sb + s * G1_STAGE, fb = bar_full1 + 8 * s;
        if (it > 0) { const long long c0 = clock64(); while (clock64() - c0 < 400) {} }
        mbar_expect_tx(fb, G1_STAGE);
        tma_load_2d(st, it < 4 ? &tm.x0[br] : &tm.x[br], e * 1024 + it * 64, rb * 128, fb);
        tma_load_3d(st + A_BYTES, &tm.w0[br], cg * 256, it * 64, 0, fb);
        tma_load_3d(st + A_BYTES + 12288, &tm.w0[br], cg * 256, it * 64 + 32, 0, fb);
      }
    }
    __syncwarp();
    asm volatile("barrier.cluster.wait.aligned;" ::: "memory");
    if (warp == 8) {
      if (lane == 0) {
        int s = 1, ph = 0;
        TS(15);
        for (int it = G1_STAGES; it < 64; it++) {
          const int ks = it & 15, hp = cg * 4 + (it >> 4);
          const uint32_t st = sb + s * G1_STAGE, fb = bar_full1 + 8 * s;
          mbar_wait(bar_empty1 + 8 * s, ph);
          mbar_expect_tx(fb, G1_STAGE);
          tma_load_2d(st, &tm.x[br], e * 1024 + ks * 64, rb * 128, fb);
          tma_load_3d_mc(st + A_BYTES + e * 12288, &tm.w[br], hp * 64, ks * 64 + e * 32, 0, fb, (uint16_t)3);
          if (it == 8) { prefetch_tmap(&tm.wo[br]); prefetch_tmap(&tm.out); }
          if (++s == G1_STAGES) s = 0;
          if (s == 1) ph ^= 1;
        }
        for (int it = 0; it < 16; it++) {
          const int kb = (it & 3) * 4 + (it >> 2), s2 = it & 3;
          const uint32_t st = sb + s2 * G2_STAGE, fb = bar_full2 + 8 * s2;
          if (it < G2_STAGES) {
            if (it == 0) mbar_wait(bar_empty1, 1);
            mbar_wait(bar_empty1 + 8 * (it + 1), 0);
          } else {
            mbar_wait(bar_empty2 + 8 * s2, ((it >> 2) - 1) & 1);
          }
          mbar_expect_tx(fb, G2_STAGE);
          tma_load_3d_mc(st + A_BYTES + e * 16384, &tm.wo[br], 0, kb * 64 + e * 32, cg * 4, fb, (uint16_t)3);
          if ((it & 3) == 0) mbar_wait(bar_o + 8 * (it >> 2), 0);
          bulk_load(st, g_o + (((br * 8 + rb) * 2 + e) * 16 + kb) * 1024, A_BYTES, fb);
        }
      }
    } else {
      const unsigned tag = __ldcg(&g_epoch[cta]) + 1u;
      if (warp < 11) {
        const int half = warp - 9;
        ulonglong2* dst = g_halo + (cta + 8) * 4 * 256 + half * 128 + lane;
        const ulonglong2* src = g_halo + cta * 4 * 256 + half * 128 + lane;
        if (rb < 7) {
          mbar_wait(bar_empty1 + 32, 0);
          const unsigned long long inv = (unsigned long long)(tag - 1u) << 32;
#pragma unroll 1
          for (int t = 0; t < 4; t++) {
#pragma unroll
            for (int p = 0; p < 4; p++)
              asm volatile("st.relaxed.gpu.global.v2.b64 [%0], {%1, %1};" ::"l"(dst + t * 256 + p * 32), "l"(inv) : "memory");
            __nanosleep(500);
          }
        }
#pragma unroll 1
        for (int t = 0; t < 4; t++) {
          mbar_wait(bar_x + 128 + 8 * half, t & 1);
          if (rb < 7) {
            const unsigned long long hi = (unsigned long long)tag << 32;
#pragma unroll
            for (int i = 0; i < 2; i++) {
              const uint4 v = lds128(sb + OFF_X + 8 * 2048 + half * 1024 + i * 512 + lane * 16);
              asm volatile("st.relaxed.gpu.global.v2.b64 [%0], {%1, %2};" ::"l"(dst + t * 256 + i * 64), "l"(hi | v.x), "l"(hi | v.y) : "memory");
              asm volatile("st.relaxed.gpu.global.v2.b64 [%0], {%1, %2};" ::"l"(dst + t * 256 + i * 64 + 32), "l"(hi | v.z), "l"(hi | v.w) : "memory");
            }
          }
          __syncwarp();
          if (lane == 0) mbar_arrive(bar_o_empty);
          unsigned long long v[8];
          if (rb > 0) {
            uint32_t spins = 0;
            while (true) {
#pragma unroll
              for (int p = 0; p < 4; p++)
                asm volatile("ld.relaxed.gpu.global.v2.b64 {%0, %1}, [%2];" : "=l"(v[2 * p]), "=l"(v[2 * p + 1])
                             : "l"(src + t * 256 + p * 32) : "memory");
              bool ok = true;
#pragma unroll
              for (int p = 0; p < 8; p++) ok &= (unsigned)(v[p] >> 32) == tag;
              if (__all_sync(0xffffffffu, ok)) break;
              if (++spins > SPIN_LIMIT) __trap();
            }
          } else {
#pragma unroll
            for (int p = 0; p < 8; p++) v[p] = 0;
          }
#pragma unroll
          for (int i = 0; i < 2; i++)
            sts128(sb + OFF_X + half * 1024 + i * 512 + lane * 16, (uint32_t)v[4 * i], (uint32_t)v[4 * i + 1], (uint32_t)v[4 * i + 2], (uint32_t)v[4 * i + 3]);
          __syncwarp();
          if (lane == 0) { mbar_arrive(bar_x + 8 * half); if (t == 3) TS(30 + half); }
        }
      } else if (lane == 0) {
        unsigned* flag = &g_o_ready[((br * 8 + rb) * 2 + e) * 4];
        uint4* dst = g_o + (((br * 8 + rb) * 2 + e) * 16 + cg * 4) * 1024;
#pragma unroll 1
        for (int t = 0; t < 4; t++, flag++) {
          mbar_wait(bar_o_full, t & 1);
          TS(16 + t);
#pragma unroll 1
          for (int i = 0; i < 8; i++, dst += 128) {
            bulk_store(dst, sb + OFF_X + i * 2048, 2048);
            if (i < 7) __nanosleep(t < 3 ? 80 : 50);
          }
          bulk_commit();
          bulk_wait0_read();
          mbar_arrive(bar_o_empty);
          bulk_wait0();
          asm volatile("red.release.gpu.global.add.u32 [%0], 1;" ::"l"(flag) : "memory");
          TS(20 + t);
          wait_flag(flag, tag * 4u);
          asm volatile("fence.proxy.async.global;" ::: "memory");
          mbar_arrive(bar_o + 8 * t);
          TS(24 + t);
        }
      }
    }
  }
}

typedef CUresult (*EncodeFn)(CUtensorMap*, CUtensorMapDataType, cuuint32_t, void*, const cuuint64_t*, const cuuint64_t*,
                             const cuuint32_t*, const cuuint32_t*, CUtensorMapInterleave, CUtensorMapSwizzle,
                             CUtensorMapL2promotion, CUtensorMapFloatOOBfill);

bool encode(EncodeFn fn, CUtensorMap* m, const void* ptr, int rank, const cuuint64_t* dims, const cuuint64_t* strides,
            const cuuint32_t* box, CUtensorMapL2promotion promo = CU_TENSOR_MAP_L2_PROMOTION_L2_256B) {
  const cuuint32_t es[3] = {1, 1, 1};
  return fn(m, CU_TENSOR_MAP_DATA_TYPE_BFLOAT16, rank, const_cast<void*>(ptr), dims, strides, box, es,
            CU_TENSOR_MAP_INTERLEAVE_NONE, CU_TENSOR_MAP_SWIZZLE_128B, promo,
            CU_TENSOR_MAP_FLOAT_OOB_FILL_NONE) == CUDA_SUCCESS;
}

}

extern "C" void kernel_launch(void* const* d_in, const int* in_sizes, int n_in, void* d_out, int out_size) {
  (void)in_sizes; (void)n_in; (void)out_size;
  void* fp = nullptr;
  cudaDriverEntryPointQueryResult qr;
  if (cudaGetDriverEntryPoint("cuTensorMapEncodeTiled", &fp, cudaEnableDefault, &qr) != cudaSuccess || !fp) return;
  EncodeFn fn = (EncodeFn)fp;
  TMaps tm;
  tm.zero = 0;
  bool ok = true;
  for (int b = 0; b < 2; b++) {
    tm.xp[b] = d_in[3 * b]; tm.wp[b] = d_in[3 * b + 1];
    {
      const cuuint64_t dims[2] = {2048, 1024}, str[1] = {4096};
      const cuuint32_t box[2] = {64, 128};
      ok &= encode(fn, &tm.x[b], d_in[3 * b + 0], 2, dims, str, box);
      ok &= encode(fn, &tm.x0[b], d_in[3 * b + 0], 2, dims, str, box, CU_TENSOR_MAP_L2_PROMOTION_L2_128B);
    }
    {
      const cuuint64_t dims[3] = {1024, 1024, 3}, str[2] = {6144, 2048};
      const cuuint32_t box[3] = {64, 32, 3};
      ok &= encode(fn, &tm.w[b], d_in[3 * b + 1], 3, dims, str, box);
      ok &= encode(fn, &tm.w0[b], d_in[3 * b + 1], 3, dims, str, box, CU_TENSOR_MAP_L2_PROMOTION_L2_128B);
    }
    {
      const cuuint64_t dims[3] = {64, 1024, 16}, str[2] = {2048, 128};
      const cuuint32_t box[3] = {64, 32, 4};
      ok &= encode(fn, &tm.wo[b], d_in[3 * b + 2], 3, dims, str, box);
    }
  }
  {
    const cuuint64_t dims[2] = {4096, 1024}, str[1] = {8192};
    const cuuint32_t box[2] = {64, 16};
    ok &= encode(fn, &tm.out, d_out, 2, dims, str, box);
  }
  if (!ok) return;
  cudaFuncSetAttribute(fused_kernel, cudaFuncAttributeMaxDynamicSharedMemorySize, SMEM_BYTES);
  fused_kernel<<<NUM_CTAS, NUM_THREADS, SMEM_BYTES>>>(tm);
}
```

```cpp
#include <cuda_runtime.h>
#include <cuda_bf16.h>
#include <cuda.h>
#include <stdint.h>
#include <type_traits>

namespace {

__device__ __forceinline__ void wgmma_n192(float (&d)[128], uint64_t da, uint64_t db, int scale_d) {
  asm volatile("{\n.reg .pred p;\nsetp.ne.b32 p, %98, 0;\n"
    "wgmma.mma_async.sync.aligned.m64n192k16.f32.bf16.bf16 "
    "{%0, %1, %2, %3, %4, %5, %6, %7, %8, %9, %10, %11, %12, %13, %14, %15, "
    "%16, %17, %18, %19, %20, %21, %22, %23, %24, %25, %26, %27, %28, %29, %30, %31, "
    "%32, %33, %34, %35, %36, %37, %38, %39, %40, %41, %42, %43, %44, %45, %46, %47, "
    "%48, %49, %50, %51, %52, %53, %54, %55, %56, %57, %58, %59, %60, %61, %62, %63, "
    "%64, %65, %66, %67, %68, %69, %70, %71, %72, %73, %74, %75, %76, %77, %78, %79, "
    "%80, %81, %82, %83, %84, %85, %86, %87, %88, %89, %90, %91, %92, %93, %94, %95}, "
    "%96, %97, p, 1, 1, 0, 1;\n}\n"
    : "+f"(d[0]), "+f"(d[1]), "+f"(d[2]), "+f"(d[3]), "+f"(d[4]), "+f"(d[5]), "+f"(d[6]), "+f"(d[7]),
      "+f"(d[8]), "+f"(d[9]), "+f"(d[10]), "+f"(d[11]), "+f"(d[12]), "+f"(d[13]), "+f"(d[14]), "+f"(d[15]),
      "+f"(d[16]), "+f"(d[17]), "+f"(d[18]), "+f"(d[19]), "+f"(d[20]), "+f"(d[21]), "+f"(d[22]), "+f"(d[23]),
      "+f"(d[24]), "+f"(d[25]), "+f"(d[26]), "+f"(d[27]), "+f"(d[28]), "+f"(d[29]), "+f"(d[30]), "+f"(d[31]),
      "+f"(d[32]), "+f"(d[33]), "+f"(d[34]), "+f"(d[35]), "+f"(d[36]), "+f"(d[37]), "+f"(d[38]), "+f"(d[39]),
      "+f"(d[40]), "+f"(d[41]), "+f"(d[42]), "+f"(d[43]), "+f"(d[44]), "+f"(d[45]), "+f"(d[46]), "+f"(d[47]),
      "+f"(d[48]), "+f"(d[49]), "+f"(d[50]), "+f"(d[51]), "+f"(d[52]), "+f"(d[53]), "+f"(d[54]), "+f"(d[55]),
      "+f"(d[56]), "+f"(d[57]), "+f"(d[58]), "+f"(d[59]), "+f"(d[60]), "+f"(d[61]), "+f"(d[62]), "+f"(d[63]),
      "+f"(d[64]), "+f"(d[65]), "+f"(d[66]), "+f"(d[67]), "+f"(d[68]), "+f"(d[69]), "+f"(d[70]), "+f"(d[71]),
      "+f"(d[72]), "+f"(d[73]), "+f"(d[74]), "+f"(d[75]), "+f"(d[76]), "+f"(d[77]), "+f"(d[78]), "+f"(d[79]),
      "+f"(d[80]), "+f"(d[81]), "+f"(d[82]), "+f"(d[83]), "+f"(d[84]), "+f"(d[85]), "+f"(d[86]), "+f"(d[87]),
      "+f"(d[88]), "+f"(d[89]), "+f"(d[90]), "+f"(d[91]), "+f"(d[92]), "+f"(d[93]), "+f"(d[94]), "+f"(d[95])
    : "l"(da), "l"(db), "r"(scale_d));
}

__device__ __forceinline__ void wgmma_n256(float (&d)[128], uint64_t da, uint64_t db, int scale_d) {
  asm volatile("{\n.reg .pred p;\nsetp.ne.b32 p, %130, 0;\n"
    "wgmma.mma_async.sync.aligned.m64n256k16.f32.bf16.bf16 "
    "{%0, %1, %2, %3, %4, %5, %6, %7, %8, %9, %10, %11, %12, %13, %14, %15, "
    "%16, %17, %18, %19, %20, %21, %22, %23, %24, %25, %26, %27, %28, %29, %30, %31, "
    "%32, %33, %34, %35, %36, %37, %38, %39, %40, %41, %42, %43, %44, %45, %46, %47, "
    "%48, %49, %50, %51, %52, %53, %54, %55, %56, %57, %58, %59, %60, %61, %62, %63, "
    "%64, %65, %66, %67, %68, %69, %70, %71, %72, %73, %74, %75, %76, %77, %78, %79, "
    "%80, %81, %82, %83, %84, %85, %86, %87, %88, %89, %90, %91, %92, %93, %94, %95, "
    "%96, %97, %98, %99, %100, %101, %102, %103, %104, %105, %106, %107, %108, %109, %110, %111, "
    "%112, %113, %114, %115, %116, %117, %118, %119, %120, %121, %122, %123, %124, %125, %126, %127}, "
    "%128, %129, p, 1, 1, 0, 1;\n}\n"
    : "+f"(d[0]), "+f"(d[1]), "+f"(d[2]), "+f"(d[3]), "+f"(d[4]), "+f"(d[5]), "+f"(d[6]), "+f"(d[7]),
      "+f"(d[8]), "+f"(d[9]), "+f"(d[10]), "+f"(d[11]), "+f"(d[12]), "+f"(d[13]), "+f"(d[14]), "+f"(d[15]),
      "+f"(d[16]), "+f"(d[17]), "+f"(d[18]), "+f"(d[19]), "+f"(d[20]), "+f"(d[21]), "+f"(d[22]), "+f"(d[23]),
      "+f"(d[24]), "+f"(d[25]), "+f"(d[26]), "+f"(d[27]), "+f"(d[28]), "+f"(d[29]), "+f"(d[30]), "+f"(d[31]),
      "+f"(d[32]), "+f"(d[33]), "+f"(d[34]), "+f"(d[35]), "+f"(d[36]), "+f"(d[37]), "+f"(d[38]), "+f"(d[39]),
      "+f"(d[40]), "+f"(d[41]), "+f"(d[42]), "+f"(d[43]), "+f"(d[44]), "+f"(d[45]), "+f"(d[46]), "+f"(d[47]),
      "+f"(d[48]), "+f"(d[49]), "+f"(d[50]), "+f"(d[51]), "+f"(d[52]), "+f"(d[53]), "+f"(d[54]), "+f"(d[55]),
      "+f"(d[56]), "+f"(d[57]), "+f"(d[58]), "+f"(d[59]), "+f"(d[60]), "+f"(d[61]), "+f"(d[62]), "+f"(d[63]),
      "+f"(d[64]), "+f"(d[65]), "+f"(d[66]), "+f"(d[67]), "+f"(d[68]), "+f"(d[69]), "+f"(d[70]), "+f"(d[71]),
      "+f"(d[72]), "+f"(d[73]), "+f"(d[74]), "+f"(d[75]), "+f"(d[76]), "+f"(d[77]), "+f"(d[78]), "+f"(d[79]),
      "+f"(d[80]), "+f"(d[81]), "+f"(d[82]), "+f"(d[83]), "+f"(d[84]), "+f"(d[85]), "+f"(d[86]), "+f"(d[87]),
      "+f"(d[88]), "+f"(d[89]), "+f"(d[90]), "+f"(d[91]), "+f"(d[92]), "+f"(d[93]), "+f"(d[94]), "+f"(d[95]),
      "+f"(d[96]), "+f"(d[97]), "+f"(d[98]), "+f"(d[99]), "+f"(d[100]), "+f"(d[101]), "+f"(d[102]), "+f"(d[103]),
      "+f"(d[104]), "+f"(d[105]), "+f"(d[106]), "+f"(d[107]), "+f"(d[108]), "+f"(d[109]), "+f"(d[110]), "+f"(d[111]),
      "+f"(d[112]), "+f"(d[113]), "+f"(d[114]), "+f"(d[115]), "+f"(d[116]), "+f"(d[117]), "+f"(d[118]), "+f"(d[119]),
      "+f"(d[120]), "+f"(d[121]), "+f"(d[122]), "+f"(d[123]), "+f"(d[124]), "+f"(d[125]), "+f"(d[126]), "+f"(d[127])
    : "l"(da), "l"(db), "r"(scale_d));
}

template <int O>
__device__ __forceinline__ void wgmma_n128(float (&d)[128], uint64_t da, uint64_t db, int scale_d) {
  asm volatile("{\n.reg .pred p;\nsetp.ne.b32 p, %66, 0;\n"
    "wgmma.mma_async.sync.aligned.m64n128k16.f32.bf16.bf16 "
    "{%0, %1, %2, %3, %4, %5, %6, %7, %8, %9, %10, %11, %12, %13, %14, %15, "
    "%16, %17, %18, %19, %20, %21, %22, %23, %24, %25, %26, %27, %28, %29, %30, %31, "
    "%32, %33, %34, %35, %36, %37, %38, %39, %40, %41, %42, %43, %44, %45, %46, %47, "
    "%48, %49, %50, %51, %52, %53, %54, %55, %56, %57, %58, %59, %60, %61, %62, %63}, "
    "%64, %65, p, 1, 1, 0, 1;\n}\n"
    : "+f"(d[O + 0]), "+f"(d[O + 1]), "+f"(d[O + 2]), "+f"(d[O + 3]), "+f"(d[O + 4]), "+f"(d[O + 5]), "+f"(d[O + 6]), "+f"(d[O + 7]),
      "+f"(d[O + 8]), "+f"(d[O + 9]), "+f"(d[O + 10]), "+f"(d[O + 11]), "+f"(d[O + 12]), "+f"(d[O + 13]), "+f"(d[O + 14]), "+f"(d[O + 15]),
      "+f"(d[O + 16]), "+f"(d[O + 17]), "+f"(d[O + 18]), "+f"(d[O + 19]), "+f"(d[O + 20]), "+f"(d[O + 21]), "+f"(d[O + 22]), "+f"(d[O + 23]),
      "+f"(d[O + 24]), "+f"(d[O + 25]), "+f"(d[O + 26]), "+f"(d[O + 27]), "+f"(d[O + 28]), "+f"(d[O + 29]), "+f"(d[O + 30]), "+f"(d[O + 31]),
      "+f"(d[O + 32]), "+f"(d[O + 33]), "+f"(d[O + 34]), "+f"(d[O + 35]), "+f"(d[O + 36]), "+f"(d[O + 37]), "+f"(d[O + 38]), "+f"(d[O + 39]),
      "+f"(d[O + 40]), "+f"(d[O + 41]), "+f"(d[O + 42]), "+f"(d[O + 43]), "+f"(d[O + 44]), "+f"(d[O + 45]), "+f"(d[O + 46]), "+f"(d[O + 47]),
      "+f"(d[O + 48]), "+f"(d[O + 49]), "+f"(d[O + 50]), "+f"(d[O + 51]), "+f"(d[O + 52]), "+f"(d[O + 53]), "+f"(d[O + 54]), "+f"(d[O + 55]),
      "+f"(d[O + 56]), "+f"(d[O + 57]), "+f"(d[O + 58]), "+f"(d[O + 59]), "+f"(d[O + 60]), "+f"(d[O + 61]), "+f"(d[O + 62]), "+f"(d[O + 63])
    : "l"(da), "l"(db), "r"(scale_d));
}

template <int O>
__device__ __forceinline__ void wgmma_n128_rs(float (&d)[128], const uint32_t (&a)[4], uint64_t db) {
  asm volatile("wgmma.mma_async.sync.aligned.m64n128k16.f32.bf16.bf16 "
    "{%0, %1, %2, %3, %4, %5, %6, %7, %8, %9, %10, %11, %12, %13, %14, %15, "
    "%16, %17, %18, %19, %20, %21, %22, %23, %24, %25, %26, %27, %28, %29, %30, %31, "
    "%32, %33, %34, %35, %36, %37, %38, %39, %40, %41, %42, %43, %44, %45, %46, %47, "
    "%48, %49, %50, %51, %52, %53, %54, %55, %56, %57, %58, %59, %60, %61, %62, %63}, "
    "{%64, %65, %66, %67}, %68, 1, 1, 1, 1;\n"
    : "+f"(d[O + 0]), "+f"(d[O + 1]), "+f"(d[O + 2]), "+f"(d[O + 3]), "+f"(d[O + 4]), "+f"(d[O + 5]), "+f"(d[O + 6]), "+f"(d[O + 7]),
      "+f"(d[O + 8]), "+f"(d[O + 9]), "+f"(d[O + 10]), "+f"(d[O + 11]), "+f"(d[O + 12]), "+f"(d[O + 13]), "+f"(d[O + 14]), "+f"(d[O + 15]),
      "+f"(d[O + 16]), "+f"(d[O + 17]), "+f"(d[O + 18]), "+f"(d[O + 19]), "+f"(d[O + 20]), "+f"(d[O + 21]), "+f"(d[O + 22]), "+f"(d[O + 23]),
      "+f"(d[O + 24]), "+f"(d[O + 25]), "+f"(d[O + 26]), "+f"(d[O + 27]), "+f"(d[O + 28]), "+f"(d[O + 29]), "+f"(d[O + 30]), "+f"(d[O + 31]),
      "+f"(d[O + 32]), "+f"(d[O + 33]), "+f"(d[O + 34]), "+f"(d[O + 35]), "+f"(d[O + 36]), "+f"(d[O + 37]), "+f"(d[O + 38]), "+f"(d[O + 39]),
      "+f"(d[O + 40]), "+f"(d[O + 41]), "+f"(d[O + 42]), "+f"(d[O + 43]), "+f"(d[O + 44]), "+f"(d[O + 45]), "+f"(d[O + 46]), "+f"(d[O + 47]),
      "+f"(d[O + 48]), "+f"(d[O + 49]), "+f"(d[O + 50]), "+f"(d[O + 51]), "+f"(d[O + 52]), "+f"(d[O + 53]), "+f"(d[O + 54]), "+f"(d[O + 55]),
      "+f"(d[O + 56]), "+f"(d[O + 57]), "+f"(d[O + 58]), "+f"(d[O + 59]), "+f"(d[O + 60]), "+f"(d[O + 61]), "+f"(d[O + 62]), "+f"(d[O + 63])
    : "r"(a[0]), "r"(a[1]), "r"(a[2]), "r"(a[3]), "l"(db));
}

template <int O>
__device__ __forceinline__ void wgmma_n64_rs(float (&d)[128], const uint32_t (&a)[4], uint64_t db) {
  asm volatile("wgmma.mma_async.sync.aligned.m64n64k16.f32.bf16.bf16 "
    "{%0, %1, %2, %3, %4, %5, %6, %7, %8, %9, %10, %11, %12, %13, %14, %15, "
    "%16, %17, %18, %19, %20, %21, %22, %23, %24, %25, %26, %27, %28, %29, %30, %31}, "
    "{%32, %33, %34, %35}, %36, 1, 1, 1, 1;\n"
    : "+f"(d[O + 0]), "+f"(d[O + 1]), "+f"(d[O + 2]), "+f"(d[O + 3]), "+f"(d[O + 4]), "+f"(d[O + 5]), "+f"(d[O + 6]), "+f"(d[O + 7]),
      "+f"(d[O + 8]), "+f"(d[O + 9]), "+f"(d[O + 10]), "+f"(d[O + 11]), "+f"(d[O + 12]), "+f"(d[O + 13]), "+f"(d[O + 14]), "+f"(d[O + 15]),
      "+f"(d[O + 16]), "+f"(d[O + 17]), "+f"(d[O + 18]), "+f"(d[O + 19]), "+f"(d[O + 20]), "+f"(d[O + 21]), "+f"(d[O + 22]), "+f"(d[O + 23]),
      "+f"(d[O + 24]), "+f"(d[O + 25]), "+f"(d[O + 26]), "+f"(d[O + 27]), "+f"(d[O + 28]), "+f"(d[O + 29]), "+f"(d[O + 30]), "+f"(d[O + 31])
    : "r"(a[0]), "r"(a[1]), "r"(a[2]), "r"(a[3]), "l"(db));
}

constexpr int NUM_CTAS = 128;
constexpr int NUM_THREADS = 384;
constexpr int G1_STAGES = 5, G2_STAGES = 4;
constexpr uint32_t A_BYTES = 16384;
constexpr uint32_t G1_STAGE = 40960;
constexpr uint32_t G2_STAGE = 49152;
constexpr uint32_t RING_BYTES = G1_STAGES * G1_STAGE;
constexpr uint32_t OFF_X = RING_BYTES;
constexpr uint32_t OFF_BAR = OFF_X + 9 * 2048;
constexpr uint32_t SMEM_BYTES = OFF_BAR + 512;
constexpr uint32_t SPIN_LIMIT = 1u << 21;

struct alignas(64) TMaps {
  CUtensorMap x[2], w[2], wo[2], out;
  CUtensorMap x0[2], w0[2];
  const void* xp[2];
  const void* wp[2];
  uint32_t zero;
};

__device__ uint4 g_o[32 * 16 * 1024];
__device__ ulonglong2 g_halo[NUM_CTAS * 4 * 256];
__device__ unsigned g_o_ready[32 * 4];
__device__ unsigned g_epoch[NUM_CTAS];

__device__ __forceinline__ void mbar_init(uint32_t bar, uint32_t count) {
  asm volatile("mbarrier.init.shared::cta.b64 [%0], %1;" ::"r"(bar), "r"(count) : "memory");
}
__device__ __forceinline__ bool mbar_try_wait(uint32_t bar, uint32_t parity) {
  uint32_t ok;
  asm volatile("{\n.reg .pred p;\nmbarrier.try_wait.parity.shared::cta.b64 p, [%1], %2;\nselp.u32 %0, 1, 0, p;\n}\n"
               : "=r"(ok) : "r"(bar), "r"(parity) : "memory");
  return ok != 0;
}
__device__ __forceinline__ void mbar_wait(uint32_t bar, uint32_t parity) {
  uint32_t spins = 0;
  while (!mbar_try_wait(bar, parity)) { if (++spins > SPIN_LIMIT) __trap(); }
}
__device__ __forceinline__ void mbar_arrive(uint32_t bar) {
  asm volatile("mbarrier.arrive.shared::cta.b64 _, [%0];" ::"r"(bar) : "memory");
}
__device__ __forceinline__ void mbar_arrive_cluster(uint32_t bar_cluster_addr) {
  asm volatile("mbarrier.arrive.shared::cluster.b64 _, [%0];" ::"r"(bar_cluster_addr) : "memory");
}
__device__ __forceinline__ void mbar_expect_tx(uint32_t bar, uint32_t bytes) {
  asm volatile("mbarrier.arrive.expect_tx.shared::cta.b64 _, [%0], %1;" ::"r"(bar), "r"(bytes) : "memory");
}
__device__ __forceinline__ uint32_t mapa(uint32_t addr, uint32_t rank) {
  uint32_t r; asm("mapa.shared::cluster.u32 %0, %1, %2;" : "=r"(r) : "r"(addr), "r"(rank)); return r;
}
__device__ __forceinline__ void tma_load_2d(uint32_t dst, const CUtensorMap* m, int c0, int c1, uint32_t bar) {
  asm volatile("cp.async.bulk.tensor.2d.shared::cluster.global.mbarrier::complete_tx::bytes [%0], [%1, {%3, %4}], [%2];"
               ::"r"(dst), "l"(m), "r"(bar), "r"(c0), "r"(c1) : "memory");
}
__device__ __forceinline__ void tma_load_3d(uint32_t dst, const CUtensorMap* m, int c0, int c1, int c2, uint32_t bar) {
  asm volatile("cp.async.bulk.tensor.3d.shared::cluster.global.mbarrier::complete_tx::bytes [%0], [%1, {%3, %4, %5}], [%2];"
               ::"r"(dst), "l"(m), "r"(bar), "r"(c0), "r"(c1), "r"(c2) : "memory");
}
__device__ __forceinline__ void tma_load_3d_mc(uint32_t dst, const CUtensorMap* m, int c0, int c1, int c2, uint32_t bar, uint16_t mask) {
  asm volatile("cp.async.bulk.tensor.3d.shared::cluster.global.mbarrier::complete_tx::bytes.multicast::cluster [%0], [%1, {%3, %4, %5}], [%2], %6;"
               ::"r"(dst), "l"(m), "r"(bar), "r"(c0), "r"(c1), "r"(c2), "h"(mask) : "memory");
}
__device__ __forceinline__ void tma_store_2d(const CUtensorMap* m, int c0, int c1, uint32_t src) {
  asm volatile("cp.async.bulk.tensor.2d.global.shared::cta.bulk_group [%0, {%2, %3}], [%1];"
               ::"l"(m), "r"(src), "r"(c0), "r"(c1) : "memory");
}
__device__ __forceinline__ void bulk_load(uint32_t dst, const void* src, uint32_t bytes, uint32_t bar) {
  asm volatile("cp.async.bulk.shared::cluster.global.mbarrier::complete_tx::bytes [%0], [%1], %2, [%3];"
               ::"r"(dst), "l"(src), "r"(bytes), "r"(bar) : "memory");
}
__device__ __forceinline__ void bulk_store(void* dst, uint32_t src, uint32_t bytes) {
  asm volatile("cp.async.bulk.global.shared::cta.bulk_group [%0], [%1], %2;" ::"l"(dst), "r"(src), "r"(bytes) : "memory");
}
__device__ __forceinline__ void bulk_commit() { asm volatile("cp.async.bulk.commit_group;" ::: "memory"); }
__device__ __forceinline__ void bulk_wait0() { asm volatile("cp.async.bulk.wait_group 0;" ::: "memory"); }
__device__ __forceinline__ void bulk_wait0_read() { asm volatile("cp.async.bulk.wait_group.read 0;" ::: "memory"); }
__device__ __forceinline__ void fence_async_smem() { asm volatile("fence.proxy.async.shared::cta;" ::: "memory"); }
__device__ __forceinline__ void prefetch_tmap(const CUtensorMap* m) {
  asm volatile("prefetch.tensormap [%0];" ::"l"(m) : "memory");
}
__device__ __forceinline__ void wgmma_fence() { asm volatile("wgmma.fence.sync.aligned;" ::: "memory"); }
__device__ __forceinline__ void wgmma_commit() { asm volatile("wgmma.commit_group.sync.aligned;" ::: "memory"); }
template <int N> __device__ __forceinline__ void wgmma_wait() { asm volatile("wgmma.wait_group.sync.aligned %0;" ::"n"(N) : "memory"); }
template <int B, int N> __device__ __forceinline__ void fence_acc(float (&d)[128]) {
#pragma unroll
  for (int i = B; i < N; i++) asm volatile("" : "+f"(d[i])::"memory");
}
__device__ __forceinline__ void bar_sync(int id) { asm volatile("bar.sync %0, 256;" ::"r"(id) : "memory"); }
__device__ __forceinline__ void bar_arrive(int id) { asm volatile("bar.arrive %0, 256;" ::"r"(id) : "memory"); }
__device__ __forceinline__ uint64_t desc_kmajor(uint32_t addr) {
  return (uint64_t)((addr & 0x3FFFF) >> 4) | (1ull << 16) | (64ull << 32) | (1ull << 62);
}
__device__ __forceinline__ uint64_t desc_mnmajor(uint32_t addr) {
  return (uint64_t)((addr & 0x3FFFF) >> 4) | (256ull << 16) | (64ull << 32) | (1ull << 62);
}
__device__ __forceinline__ uint32_t pack_bf16(float lo, float hi) {
  uint32_t r; asm("cvt.rn.bf16x2.f32 %0, %1, %2;" : "=r"(r) : "f"(hi), "f"(lo)); return r;
}
__device__ __forceinline__ void stsm_x4(uint32_t addr, uint32_t r0, uint32_t r1, uint32_t r2, uint32_t r3) {
  asm volatile("stmatrix.sync.aligned.m8n8.x4.shared.b16 [%0], {%1, %2, %3, %4};" ::"r"(addr), "r"(r0), "r"(r1), "r"(r2), "r"(r3) : "memory");
}
__device__ __forceinline__ void stsm_x4_t(uint32_t addr, uint32_t r0, uint32_t r1, uint32_t r2, uint32_t r3) {
  asm volatile("stmatrix.sync.aligned.m8n8.x4.trans.shared.b16 [%0], {%1, %2, %3, %4};" ::"r"(addr), "r"(r0), "r"(r1), "r"(r2), "r"(r3) : "memory");
}
__device__ __forceinline__ void ldsm_x4(uint32_t addr, uint32_t (&r)[4]) {
  asm volatile("ldmatrix.sync.aligned.m8n8.x4.shared.b16 {%0, %1, %2, %3}, [%4];" : "=r"(r[0]), "=r"(r[1]), "=r"(r[2]), "=r"(r[3]) : "r"(addr) : "memory");
}
__device__ __forceinline__ uint32_t movm_t(uint32_t a) {
  uint32_t d; asm volatile("movmatrix.sync.aligned.m8n8.trans.b16 %0, %1;" : "=r"(d) : "r"(a)); return d;
}
__device__ __forceinline__ void mma_init(float (&c)[4], uint32_t a0, uint32_t a1, uint32_t a2, uint32_t a3, uint32_t b0, uint32_t b1) {
  asm volatile("mma.sync.aligned.m16n8k16.row.col.f32.bf16.bf16.f32 {%0, %1, %2, %3}, {%4, %5, %6, %7}, {%8, %9}, {%10, %10, %10, %10};"
               : "=f"(c[0]), "=f"(c[1]), "=f"(c[2]), "=f"(c[3]) : "r"(a0), "r"(a1), "r"(a2), "r"(a3), "r"(b0), "r"(b1), "f"(0.f));
}
__device__ __forceinline__ void mma_acc(float (&c)[4], uint32_t a0, uint32_t a1, uint32_t a2, uint32_t a3, uint32_t b0, uint32_t b1) {
  asm volatile("mma.sync.aligned.m16n8k16.row.col.f32.bf16.bf16.f32 {%0, %1, %2, %3}, {%4, %5, %6, %7}, {%8, %9}, {%0, %1, %2, %3};"
               : "+f"(c[0]), "+f"(c[1]), "+f"(c[2]), "+f"(c[3]) : "r"(a0), "r"(a1), "r"(a2), "r"(a3), "r"(b0), "r"(b1));
}
__device__ __forceinline__ float ex2(float x) { float y; asm("ex2.approx.ftz.f32 %0, %1;" : "=f"(y) : "f"(x)); return y; }
__device__ __forceinline__ unsigned ld_acquire(const unsigned* p) {
  unsigned v; asm volatile("ld.acquire.gpu.global.u32 %0, [%1];" : "=r"(v) : "l"(p) : "memory"); return v;
}
__device__ __forceinline__ void wait_flag(const unsigned* p, unsigned target) {
  uint32_t spins = 0;
  while ((int)(ld_acquire(p) - target) < 0) { if (++spins > SPIN_LIMIT) __trap(); __nanosleep(20); }
}
__device__ __forceinline__ uint4 lds128(uint32_t addr) {
  uint4 v; asm volatile("ld.shared.v4.u32 {%0, %1, %2, %3}, [%4];" : "=r"(v.x), "=r"(v.y), "=r"(v.z), "=r"(v.w) : "r"(addr) : "memory"); return v;
}
__device__ __forceinline__ void sts128(uint32_t addr, uint32_t a, uint32_t b, uint32_t c, uint32_t d) {
  asm volatile("st.shared.v4.u32 [%0], {%1, %2, %3, %4};" ::"r"(addr), "r"(a), "r"(b), "r"(c), "r"(d) : "memory");
}

template <int N>
__device__ __forceinline__ void softmax_exp(const float (&lo)[N][2], const float (&hi)[N][2], bool use_lo0, bool use_lo1,
                                            float (&ex)[N][2]) {
  constexpr float kScale = 0.17677669529663687f, kLog2e = 1.4426950408889634f;
  float m[N];
#pragma unroll
  for (int i = 0; i < N; i++) {
    uint32_t p = pack_bf16(use_lo0 ? lo[i][0] : hi[i][0], use_lo1 ? lo[i][1] : hi[i][1]);
    p = pack_bf16(__uint_as_float(p << 16) * kScale, __uint_as_float(p & 0xffff0000u) * kScale);
    ex[i][0] = __uint_as_float(p << 16);
    ex[i][1] = __uint_as_float(p & 0xffff0000u);
    m[i] = fmaxf(ex[i][0], ex[i][1]);
  }
#pragma unroll
  for (int i = 0; i < N; i++) m[i] = fmaxf(m[i], __shfl_xor_sync(0xffffffffu, m[i], 1));
#pragma unroll
  for (int i = 0; i < N; i++) m[i] = fmaxf(m[i], __shfl_xor_sync(0xffffffffu, m[i], 2));
#pragma unroll
  for (int i = 0; i < N; i++) { ex[i][0] = ex2((ex[i][0] - m[i]) * kLog2e); ex[i][1] = ex2((ex[i][1] - m[i]) * kLog2e); }
}
template <int N>
__device__ __forceinline__ void softmax_norm(const float (&ex)[N][2], uint32_t lo_mask, uint32_t (&b_lo)[N], uint32_t (&b_hi)[N]) {
  float s[N];
#pragma unroll
  for (int i = 0; i < N; i++) s[i] = ex[i][0] + ex[i][1];
#pragma unroll
  for (int i = 0; i < N; i++) s[i] += __shfl_xor_sync(0xffffffffu, s[i], 1);
#pragma unroll
  for (int i = 0; i < N; i++) s[i] += __shfl_xor_sync(0xffffffffu, s[i], 2);
#pragma unroll
  for (int i = 0; i < N; i++) {
    float r;
    asm("rcp.approx.ftz.f32 %0, %1;" : "=f"(r) : "f"(s[i]));
    const uint32_t p = pack_bf16(ex[i][0] * r, ex[i][1] * r);
    b_lo[i] = p & lo_mask;
    b_hi[i] = p & ~lo_mask;
  }
}

__global__ void __cluster_dims__(2, 1, 1) __launch_bounds__(NUM_THREADS, 1)
fused_kernel(const __grid_constant__ TMaps tm) {
  extern __shared__ __align__(1024) uint8_t smem_raw[];
  const uint32_t sb = (uint32_t)__cvta_generic_to_shared(smem_raw);
  const int warp = __shfl_sync(0xffffffffu, threadIdx.x >> 5, 0), lane = threadIdx.x & 31;
  const int e = blockIdx.x & 1;
  int cg, rb, br;
  {
    const int c = blockIdx.x >> 1;
    int q, i;
    if (c < 4) { q = 0; i = c; }
    else if (c < 36) { q = 1 + ((c - 4) & 7); i = (c - 4) >> 3; }
    else { q = 9 + (c - 36) % 7; i = (c - 36) / 7; }
    cg = i; rb = q & 7; br = q >> 3;
  }
  const int cta = e + 2 * cg + 8 * rb + 64 * br;
  const uint32_t bar_full1 = sb + OFF_BAR, bar_empty1 = bar_full1 + 64, bar_full2 = bar_full1 + 128,
                 bar_empty2 = bar_full1 + 160, bar_o_full = bar_full1 + 192, bar_o_empty = bar_full1 + 200,
                 bar_o = bar_full1 + 208  , bar_x = bar_full1 + 240  ;

  if (warp == 8 && lane == 0) {
    prefetch_tmap(&tm.x0[br]); prefetch_tmap(&tm.w0[br]);
    prefetch_tmap(&tm.x[br]); prefetch_tmap(&tm.w[br]);
    for (int s = 0; s < G1_STAGES; s++) mbar_init(bar_full1 + 8 * s, 1);
    asm volatile("fence.mbarrier_init.release.cluster;" ::: "memory");
  } else if (warp == 9 && lane == 0) {
    for (int s = 0; s < G1_STAGES; s++) mbar_init(bar_empty1 + 8 * s, 16);
    for (int s = 0; s < G2_STAGES; s++) { mbar_init(bar_full2 + 8 * s, 1); mbar_init(bar_empty2 + 8 * s, 16); }
    for (int s = 0; s < 18; s++) mbar_init(bar_x + 8 * s, 1);
    mbar_init(bar_o_full, 8); mbar_init(bar_o_empty, 3);
    for (int t = 0; t < 4; t++) mbar_init(bar_o + 8 * t, 1);
    asm volatile("fence.mbarrier_init.release.cluster;" ::: "memory");
  } else if (warp < 2) {
    if (warp == 0) {
      const char* p = (const char*)tm.xp[br] + (size_t)(rb * 128 + cg * 32 + lane) * 4096 + e * 2048;
      asm volatile("prefetch.global.L2 [%0];" ::"l"(p));
    } else if (lane < 12) {
      const int l = rb * 2 + e + 16 * lane;
      const char* p = (const char*)tm.wp[br] + (size_t)(l / 3) * 6144 + (l % 3) * 2048 + cg * 512;
      asm volatile("prefetch.global.L2 [%0];" ::"l"(p));
    }
  }
  __syncwarp();
  asm volatile("barrier.cluster.arrive.relaxed.aligned;" ::: "memory");

  if (warp < 8) {
    asm volatile("setmaxnreg.inc.sync.aligned.u32 232;");
    asm volatile("barrier.cluster.wait.aligned;" ::: "memory");
    const int wg = warp >> 2;
    float acc[128], acc2[128];
    uint32_t pk[48];
    float of[8][4];
    uint32_t xp[8];
    float pe[4][2];
    uint32_t b_lo[4], b_hi[4];
    const bool rel_any = lane < 2;
    const uint32_t rel_base = mapa(bar_full1, lane == 0 ? e : (e ^ 1));
    const int g = lane >> 2, tq = lane & 3;
    const bool use_lo0 = (2 * tq) > g, use_lo1 = (2 * tq + 1) > g;
    const uint32_t lo_mask = (use_lo0 ? 0xffffu : 0u) | (use_lo1 ? 0xffff0000u : 0u);
    const bool seq_start = (rb == 0 && warp == 0);
    const uint32_t slot = sb + OFF_X + warp * 2048;
    int s = 1, ph = 0;

    enum { XK = 1, MH = 2, XV = 4, ML = 8, RK = 16, S1 = 32, S2 = 64, RV = 128, ST0 = 256, ST1 = 512, QK = 1024, PV = 2048 };
    auto attn = [&](auto phase, int ta) __attribute__((always_inline)) {
      constexpr int P = decltype(phase)::value;
      if constexpr ((P & XK) != 0) {
        if (ta > 0) mbar_wait(bar_o_empty, (ta - 1) & 1);
        sts128(slot + 2048 + lane * 16, pk[17], pk[19], pk[21], pk[23]);
        sts128(slot + 2560 + lane * 16, pk[25], pk[27], pk[29], pk[31]);
        __syncwarp();
        if (lane == 0) mbar_arrive(bar_x + 16 * warp + 16);
      }
      if constexpr ((P & MH) != 0) {
#pragma unroll
        for (int i = 1; i < 16; i += 2) pk[32 + i] = movm_t(pk[32 + i]);
      }
      if constexpr ((P & XV) != 0) {
        sts128(slot + 3072 + lane * 16, pk[33], pk[35], pk[37], pk[39]);
        sts128(slot + 3584 + lane * 16, pk[41], pk[43], pk[45], pk[47]);
        __syncwarp();
        if (lane == 0) mbar_arrive(bar_x + 16 * warp + 24);
      }
      if constexpr ((P & ML) != 0) {
#pragma unroll
        for (int i = 0; i < 16; i += 2) pk[32 + i] = movm_t(pk[32 + i]);
      }
      if constexpr ((P & S1) != 0) {
        if (seq_start) of[0][0] = of[0][1] = of[3][0] = of[3][1] = -INFINITY;
        const float lo[4][2] = {{of[0][0], of[0][1]}, {of[1][2], of[1][3]}, {of[3][0], of[3][1]}, {of[4][2], of[4][3]}};
        const float hi[4][2] = {{of[1][0], of[1][1]}, {of[2][2], of[2][3]}, {of[4][0], of[4][1]}, {of[5][2], of[5][3]}};
        softmax_exp<4>(lo, hi, use_lo0, use_lo1, pe);
      }
      if constexpr ((P & S2) != 0) softmax_norm<4>(pe, lo_mask, b_lo, b_hi);
      if constexpr ((P & (RK | RV)) != 0) {
        constexpr int V = (P & RV) != 0;
        mbar_wait(bar_x + 16 * warp + 8 * V, ta & 1);
        const uint4 x0 = lds128(slot + V * 1024 + lane * 16), x1 = lds128(slot + V * 1024 + 512 + lane * 16);
        xp[0] = x0.x; xp[1] = x0.y; xp[2] = x0.z; xp[3] = x0.w; xp[4] = x1.x; xp[5] = x1.y; xp[6] = x1.z; xp[7] = x1.w;
      }
      if constexpr ((P & (ST0 | ST1)) != 0) {
#pragma unroll
        for (int i = (P & ST0) ? 0 : 2; i < ((P & ST1) ? 4 : 2); i++)
          stsm_x4_t(slot + ((i & 1) * 8 + (lane & 7)) * 128 + ((((i >> 1) * 4 + (lane >> 3)) ^ (lane & 7)) << 4),
                    pack_bf16(of[2 * i][0], of[2 * i][1]), pack_bf16(of[2 * i][2], of[2 * i][3]),
                    pack_bf16(of[2 * i + 1][0], of[2 * i + 1][1]), pack_bf16(of[2 * i + 1][2], of[2 * i + 1][3]));
        if constexpr ((P & ST1) != 0) {
          fence_async_smem();
          __syncwarp();
          if (lane == 0) mbar_arrive(bar_o_full);
        }
      }
    };
    auto burst = [&](auto phase, auto from, auto to) __attribute__((always_inline)) {
      constexpr int P = decltype(phase)::value, B = decltype(from)::value, E = decltype(to)::value;
#pragma unroll
      for (int n = B; n < E; n++) {
        if constexpr (P == QK) {
          const int k = n / 6, h = (n % 6) / 3, j = n % 3, q = 8 * h + 4 * k;
          const uint32_t b0 = j == 0 ? xp[4 * h + 2 * k] : pk[15 + q + j], b1 = j == 0 ? xp[4 * h + 2 * k + 1] : pk[17 + q + j];
          if (k == 0) mma_init(of[3 * h + j], pk[q], pk[q + 1], pk[q + 2], pk[q + 3], b0, b1);
          else mma_acc(of[3 * h + j], pk[q], pk[q + 1], pk[q + 2], pk[q + 3], b0, b1);
        } else {
          const int h = n / 4, hf = (n / 2) & 1, d = n & 1, v = 32 + 8 * h + 4 * d;
          if (hf == 0) mma_init(of[n], xp[4 * h + 2 * d], xp[4 * h + 2 * d + 1], pk[v], pk[v + 2], b_lo[2 * h], b_hi[2 * h]);
          else mma_init(of[n], pk[v], pk[v + 2], pk[v + 1], pk[v + 3], b_lo[2 * h + 1], b_hi[2 * h + 1]);
        }
      }
    };
#define PH(n) std::integral_constant<int, n>{}
    uint32_t rel = 0;
    auto kstep = [&](auto g2, auto pre0, auto post, auto burst1, bool first, bool do_attn, int ta, bool next_g2) __attribute__((always_inline)) {
      constexpr bool G2 = decltype(g2)::value;
      constexpr uint32_t STAGE = G2 ? G2_STAGE : G1_STAGE;
      constexpr uint64_t HALF = G2 ? 1024 : 768;
      const uint64_t da = desc_kmajor(sb + s * STAGE + wg * 8192);
      const uint64_t db = desc_mnmajor(sb + s * STAGE + A_BYTES);
      if constexpr (decltype(pre0)::value != 0) { if (do_attn && wg == 0) burst(pre0, PH(0), PH(decltype(pre0)::value == QK ? 12 : 8)); }
      bar_sync(1 + wg);
      wgmma_fence();
      if constexpr (G2) {
        wgmma_n256(acc2, da, db, !first);
        wgmma_n256(acc2, da + 2, db + 128, 1);
        wgmma_n256(acc2, da + 4, db + HALF, 1);
        wgmma_n256(acc2, da + 6, db + HALF + 128, 1);
      } else {
        wgmma_n192(acc, da, db, !first);
        wgmma_n192(acc, da + 2, db + 128, 1);
        wgmma_n192(acc, da + 4, db + HALF, 1);
        wgmma_n192(acc, da + 6, db + HALF + 128, 1);
      }
      wgmma_commit();
      const bool late = decltype(burst1)::value != 0 && do_attn && wg == 1;
      if (!late) bar_arrive(2 - wg);
      if (rel) mbar_arrive_cluster(rel);
      rel = rel_any ? rel_base + (G2 ? 160 : 64) + 8 * s : 0;
      if constexpr (decltype(post)::value != 0) { if (do_attn) attn(post, ta); }
      if (++s == (G2 ? G2_STAGES : G1_STAGES)) s = 0;
      if (s == (G2 ? 0 : 1)) ph ^= 1;
      if (!G2 && next_g2) { s = 0; ph = 0; }
      mbar_wait((next_g2 ? bar_full2 : bar_full1) + 8 * s, ph);
      if constexpr (decltype(burst1)::value != 0) {
        if (late) {
          constexpr int N = decltype(burst1)::value == QK ? 12 : 8, M = decltype(burst1)::value == QK ? 7 : 5;
          burst(burst1, PH(0), PH(N - M));
          if (tm.zero) __trap();
          bar_arrive(1);
          burst(burst1, PH(N - M), PH(N));
        }
      }
      wgmma_wait<0>();
    };
    using F = std::false_type; using T = std::true_type;
    if (wg == 1) bar_arrive(1);
    mbar_wait(bar_full1 + 8 * s, ph);

    constexpr int sc1[11] = {0, XK, MH, XV, ML, RK | QK, S1, S2, RV | PV, ST0, ST1};
    constexpr int sc2[7] = {0, XK | MH, XV, ML, RK | QK, S1 | S2 | RV | PV, ST0 | ST1};
#define KSTEP(g2, sc, i, first, at, ta, next) \
    kstep(g2, PH(sc[i] & (QK | PV)), PH(sc[i + 1] & ~(QK | PV)), PH(sc[i + 1] & (QK | PV)), first, at, ta, next)
#pragma unroll 1
    for (int t = 0; t < 4; t++) {
      const bool at = t > 0;
      KSTEP(F{}, sc1, 0, true, at, t - 1, 0);  KSTEP(F{}, sc1, 1, false, at, t - 1, 0); KSTEP(F{}, sc1, 2, false, at, t - 1, 0);
      KSTEP(F{}, sc1, 3, false, at, t - 1, 0); KSTEP(F{}, sc1, 4, false, at, t - 1, 0); KSTEP(F{}, sc1, 5, false, at, t - 1, 0);
      KSTEP(F{}, sc1, 6, false, at, t - 1, 0); KSTEP(F{}, sc1, 7, false, at, t - 1, 0); KSTEP(F{}, sc1, 8, false, at, t - 1, 0);
      KSTEP(F{}, sc1, 9, false, at, t - 1, 0);
#pragma unroll 1
      for (int ks = 10; ks < 16; ks++) kstep(F{}, PH(0), PH(0), PH(0), false, false, 0, t == 3 && ks == 15);
      fence_acc<0, 96>(acc);
#pragma unroll
      for (int i = 0; i < 48; i++) pk[i] = pack_bf16(acc[2 * i], acc[2 * i + 1]);
    }
    KSTEP(T{}, sc2, 0, true, true, 3, 1);  KSTEP(T{}, sc2, 1, false, true, 3, 1); KSTEP(T{}, sc2, 2, false, true, 3, 1);
    KSTEP(T{}, sc2, 3, false, true, 3, 1); KSTEP(T{}, sc2, 4, false, true, 3, 1); KSTEP(T{}, sc2, 5, false, true, 3, 1);
#pragma unroll 1
    for (int ks = 6; ks < 12; ks++) kstep(T{}, PH(0), PH(0), PH(0), false, false, 0, true);
    if (rel) mbar_arrive_cluster(rel);
    auto store_chunk = [&](auto chunk, float (&ac)[128]) __attribute__((always_inline)) {
      constexpr int c = decltype(chunk)::value;
      const uint32_t stg = sb + c * G2_STAGE + warp * 2048;
      const int r = ((lane >> 3) & 1) * 8 + (lane & 7);
#pragma unroll
      for (int jj = 0; jj < 8; jj += 2) {
        const int j = c * 8 + jj;
        stsm_x4(stg + r * 128 + (((jj + (lane >> 4)) ^ (r & 7)) << 4), pack_bf16(ac[4 * j], ac[4 * j + 1]),
                pack_bf16(ac[4 * j + 2], ac[4 * j + 3]), pack_bf16(ac[4 * j + 4], ac[4 * j + 5]),
                pack_bf16(ac[4 * j + 6], ac[4 * j + 7]));
      }
      fence_async_smem();
      __syncwarp();
      if (lane == 0) {
        tma_store_2d(&tm.out, e * 2048 + br * 1024 + cg * 256 + c * 64, rb * 128 + warp * 16, stg);
        bulk_commit();
      }
    };
    if (wg == 0) {
      float acc3[128];
#pragma unroll
      for (int i = 0; i < 128; i++) asm volatile("mov.b32 %0, %1;" : "=f"(acc3[i]) : "f"(acc2[i]));
      auto half_step = [&](auto side, int j) __attribute__((always_inline)) {
        constexpr int R = decltype(side)::value;
        const uint64_t da = desc_kmajor(sb + j * G2_STAGE);
        const uint64_t db = desc_mnmajor(sb + j * G2_STAGE + A_BYTES) + R * 512;
        wgmma_n128<R * 64>(acc3, da, db, 1);
        wgmma_n128<R * 64>(acc3, da + 2, db + 128, 1);
        wgmma_n128<R * 64>(acc3, da + 4, db + 1024, 1);
        wgmma_n128<R * 64>(acc3, da + 6, db + 1024 + 128, 1);
      };
      bar_sync(1);
#pragma unroll 1
      for (int j = 0; j < 2; j++) { mbar_wait(bar_full2 + 8 * j, 1); wgmma_fence(); half_step(PH(0), j); half_step(PH(1), j); wgmma_commit(); }
#pragma unroll 1
      for (int j = 2; j < 4; j++) { mbar_wait(bar_full2 + 8 * j, 1); wgmma_fence(); half_step(PH(0), j); wgmma_commit(); }
      wgmma_fence();
      half_step(PH(1), 2); half_step(PH(1), 3);
      wgmma_commit();
      bar_arrive(2);
      wgmma_wait<1>();
      fence_acc<0, 64>(acc3);
      store_chunk(PH(0), acc3); store_chunk(PH(1), acc3);
      wgmma_wait<0>();
      fence_acc<64, 128>(acc3);
      store_chunk(PH(2), acc3); store_chunk(PH(3), acc3);
    } else {
      float acc3[128];
#pragma unroll
      for (int i = 0; i < 128; i++) asm volatile("mov.b32 %0, %1;" : "=f"(acc3[i]) : "f"(acc2[i]));
      uint32_t af[16][4];
      const int r = ((lane >> 3) & 1) * 8 + (lane & 7);
#pragma unroll
      for (int j = 0; j < 4; j++) {
        mbar_wait(bar_full2 + 8 * j, 1);
#pragma unroll
        for (int k = 0; k < 4; k++) ldsm_x4(sb + j * G2_STAGE + warp * 2048 + r * 128 + (((2 * k + (lane >> 4)) ^ (r & 7)) << 4), af[4 * j + k]);
      }
      bar_sync(2);
      wgmma_fence();
      const uint64_t db = desc_mnmajor(sb + A_BYTES);
#define B_OFF(i) (((i) >> 2) * (G2_STAGE >> 4) + (((i) >> 1) & 1) * 1024 + ((i) & 1) * 128)
#pragma unroll
      for (int i = 0; i < 16; i++) wgmma_n128_rs<0>(acc3, af[i], db + B_OFF(i));
      wgmma_commit();
#pragma unroll
      for (int i = 0; i < 16; i++) wgmma_n64_rs<64>(acc3, af[i], db + B_OFF(i) + 512);
      wgmma_commit();
      wgmma_wait<1>();
      fence_acc<0, 64>(acc3);
      store_chunk(PH(0), acc3);
      wgmma_fence();
#pragma unroll
      for (int i = 0; i < 16; i++) wgmma_n64_rs<96>(acc3, af[i], db + B_OFF(i) + 768);
      wgmma_commit();
      store_chunk(PH(1), acc3);
      wgmma_wait<1>();
      fence_acc<64, 96>(acc3);
      store_chunk(PH(2), acc3);
      wgmma_wait<0>();
      fence_acc<96, 128>(acc3);
      store_chunk(PH(3), acc3);
    }
    if (lane == 0) bulk_wait0_read();
    if (threadIdx.x == 0) { atomicAdd(&g_epoch[cta], 1u); }
  } else {
    asm volatile("setmaxnreg.dec.sync.aligned.u32 40;");
    if (warp == 8 && lane == 0) {
      fence_async_smem();
      for (int it = 0; it < G1_STAGES; it++) {
        const int s = (it + 1) % G1_STAGES;
        const uint32_t st = sb + s * G1_STAGE, fb = bar_full1 + 8 * s;
        if (it > 0) { const long long c0 = clock64(); while (clock64() - c0 < 400) {} }
        mbar_expect_tx(fb, G1_STAGE);
        tma_load_2d(st, it < 4 ? &tm.x0[br] : &tm.x[br], e * 1024 + it * 64, rb * 128, fb);
        tma_load_3d(st + A_BYTES, &tm.w0[br], cg * 256, it * 64, 0, fb);
        tma_load_3d(st + A_BYTES + 12288, &tm.w0[br], cg * 256, it * 64 + 32, 0, fb);
      }
    }
    __syncwarp();
    asm volatile("barrier.cluster.wait.aligned;" ::: "memory");
    if (warp == 8) {
      if (lane == 0) {
        int s = 1, ph = 0;
        for (int it = G1_STAGES; it < 64; it++) {
          const int ks = it & 15, hp = cg * 4 + (it >> 4);
          const uint32_t st = sb + s * G1_STAGE, fb = bar_full1 + 8 * s;
          mbar_wait(bar_empty1 + 8 * s, ph);
          mbar_expect_tx(fb, G1_STAGE);
          tma_load_2d(st, &tm.x[br], e * 1024 + ks * 64, rb * 128, fb);
          tma_load_3d_mc(st + A_BYTES + e * 12288, &tm.w[br], hp * 64, ks * 64 + e * 32, 0, fb, (uint16_t)3);
          if (it == 8) { prefetch_tmap(&tm.wo[br]); prefetch_tmap(&tm.out); }
          if (++s == G1_STAGES) s = 0;
          if (s == 1) ph ^= 1;
        }
        for (int it = 0; it < 16; it++) {
          const int kb = (it & 3) * 4 + (it >> 2), s2 = it & 3;
          const uint32_t st = sb + s2 * G2_STAGE, fb = bar_full2 + 8 * s2;
          if (it < G2_STAGES) {
            if (it == 0) mbar_wait(bar_empty1, 1);
            mbar_wait(bar_empty1 + 8 * (it + 1), 0);
          } else {
            mbar_wait(bar_empty2 + 8 * s2, ((it >> 2) - 1) & 1);
          }
          mbar_expect_tx(fb, G2_STAGE);
          tma_load_3d_mc(st + A_BYTES + e * 16384, &tm.wo[br], 0, kb * 64 + e * 32, cg * 4, fb, (uint16_t)3);
          if ((it & 3) == 0) mbar_wait(bar_o + 8 * (it >> 2), 0);
          bulk_load(st, g_o + (((br * 8 + rb) * 2 + e) * 16 + kb) * 1024, A_BYTES, fb);
        }
      }
    } else {
      const unsigned tag = __ldcg(&g_epoch[cta]) + 1u;
      if (warp < 11) {
        const int half = warp - 9;
        ulonglong2* dst = g_halo + (cta + 8) * 4 * 256 + half * 128 + lane;
        const ulonglong2* src = g_halo + cta * 4 * 256 + half * 128 + lane;
        if (rb < 7) {
          mbar_wait(bar_empty1 + 32, 0);
          const unsigned long long inv = (unsigned long long)(tag - 1u) << 32;
#pragma unroll 1
          for (int t = 0; t < 4; t++) {
#pragma unroll
            for (int p = 0; p < 4; p++)
              asm volatile("st.relaxed.gpu.global.v2.b64 [%0], {%1, %1};" ::"l"(dst + t * 256 + p * 32), "l"(inv) : "memory");
            __nanosleep(500);
          }
        }
#pragma unroll 1
        for (int t = 0; t < 4; t++) {
          mbar_wait(bar_x + 128 + 8 * half, t & 1);
          if (rb < 7) {
            const unsigned long long hi = (unsigned long long)tag << 32;
#pragma unroll
            for (int i = 0; i < 2; i++) {
              const uint4 v = lds128(sb + OFF_X + 8 * 2048 + half * 1024 + i * 512 + lane * 16);
              asm volatile("st.relaxed.gpu.global.v2.b64 [%0], {%1, %2};" ::"l"(dst + t * 256 + i * 64), "l"(hi | v.x), "l"(hi | v.y) : "memory");
              asm volatile("st.relaxed.gpu.global.v2.b64 [%0], {%1, %2};" ::"l"(dst + t * 256 + i * 64 + 32), "l"(hi | v.z), "l"(hi | v.w) : "memory");
            }
          }
          __syncwarp();
          if (lane == 0) mbar_arrive(bar_o_empty);
          unsigned long long v[8];
          if (rb > 0) {
            uint32_t spins = 0;
            while (true) {
#pragma unroll
              for (int p = 0; p < 4; p++)
                asm volatile("ld.relaxed.gpu.global.v2.b64 {%0, %1}, [%2];" : "=l"(v[2 * p]), "=l"(v[2 * p + 1])
                             : "l"(src + t * 256 + p * 32) : "memory");
              bool ok = true;
#pragma unroll
              for (int p = 0; p < 8; p++) ok &= (unsigned)(v[p] >> 32) == tag;
              if (__all_sync(0xffffffffu, ok)) break;
              if (++spins > SPIN_LIMIT) __trap();
            }
          } else {
#pragma unroll
            for (int p = 0; p < 8; p++) v[p] = 0;
          }
#pragma unroll
          for (int i = 0; i < 2; i++)
            sts128(sb + OFF_X + half * 1024 + i * 512 + lane * 16, (uint32_t)v[4 * i], (uint32_t)v[4 * i + 1], (uint32_t)v[4 * i + 2], (uint32_t)v[4 * i + 3]);
          __syncwarp();
          if (lane == 0) { mbar_arrive(bar_x + 8 * half); }
        }
      } else if (lane == 0) {
        unsigned* flag = &g_o_ready[((br * 8 + rb) * 2 + e) * 4];
        uint4* dst = g_o + (((br * 8 + rb) * 2 + e) * 16 + cg * 4) * 1024;
#pragma unroll 1
        for (int t = 0; t < 4; t++, flag++) {
          mbar_wait(bar_o_full, t & 1);
#pragma unroll 1
          for (int i = 0; i < 8; i++, dst += 128) {
            bulk_store(dst, sb + OFF_X + i * 2048, 2048);
            if (i < 7) __nanosleep(t < 3 ? 80 : 50);
          }
          bulk_commit();
          bulk_wait0_read();
          mbar_arrive(bar_o_empty);
          bulk_wait0();
          asm volatile("red.release.gpu.global.add.u32 [%0], 1;" ::"l"(flag) : "memory");
          wait_flag(flag, tag * 4u);
          asm volatile("fence.proxy.async.global;" ::: "memory");
          mbar_arrive(bar_o + 8 * t);
        }
      }
    }
  }
}

typedef CUresult (*EncodeFn)(CUtensorMap*, CUtensorMapDataType, cuuint32_t, void*, const cuuint64_t*, const cuuint64_t*,
                             const cuuint32_t*, const cuuint32_t*, CUtensorMapInterleave, CUtensorMapSwizzle,
                             CUtensorMapL2promotion, CUtensorMapFloatOOBfill);

bool encode(EncodeFn fn, CUtensorMap* m, const void* ptr, int rank, const cuuint64_t* dims, const cuuint64_t* strides,
            const cuuint32_t* box, CUtensorMapL2promotion promo = CU_TENSOR_MAP_L2_PROMOTION_L2_256B) {
  const cuuint32_t es[3] = {1, 1, 1};
  return fn(m, CU_TENSOR_MAP_DATA_TYPE_BFLOAT16, rank, const_cast<void*>(ptr), dims, strides, box, es,
            CU_TENSOR_MAP_INTERLEAVE_NONE, CU_TENSOR_MAP_SWIZZLE_128B, promo,
            CU_TENSOR_MAP_FLOAT_OOB_FILL_NONE) == CUDA_SUCCESS;
}

}

extern "C" void kernel_launch(void* const* d_in, const int* in_sizes, int n_in, void* d_out, int out_size) {
  (void)in_sizes; (void)n_in; (void)out_size;
  void* fp = nullptr;
  cudaDriverEntryPointQueryResult qr;
  if (cudaGetDriverEntryPoint("cuTensorMapEncodeTiled", &fp, cudaEnableDefault, &qr) != cudaSuccess || !fp) return;
  EncodeFn fn = (EncodeFn)fp;
  TMaps tm;
  tm.zero = 0;
  bool ok = true;
  for (int b = 0; b < 2; b++) {
    tm.xp[b] = d_in[3 * b]; tm.wp[b] = d_in[3 * b + 1];
    {
      const cuuint64_t dims[2] = {2048, 1024}, str[1] = {4096};
      const cuuint32_t box[2] = {64, 128};
      ok &= encode(fn, &tm.x[b], d_in[3 * b + 0], 2, dims, str, box);
      ok &= encode(fn, &tm.x0[b], d_in[3 * b + 0], 2, dims, str, box, CU_TENSOR_MAP_L2_PROMOTION_L2_128B);
    }
    {
      const cuuint64_t dims[3] = {1024, 1024, 3}, str[2] = {6144, 2048};
      const cuuint32_t box[3] = {64, 32, 3};
      ok &= encode(fn, &tm.w[b], d_in[3 * b + 1], 3, dims, str, box);
      ok &= encode(fn, &tm.w0[b], d_in[3 * b + 1], 3, dims, str, box, CU_TENSOR_MAP_L2_PROMOTION_L2_128B);
    }
    {
      const cuuint64_t dims[3] = {64, 1024, 16}, str[2] = {2048, 128};
      const cuuint32_t box[3] = {64, 32, 4};
      ok &= encode(fn, &tm.wo[b], d_in[3 * b + 2], 3, dims, str, box);
    }
  }
  {
    const cuuint64_t dims[2] = {4096, 1024}, str[1] = {8192};
    const cuuint32_t box[2] = {64, 16};
    ok &= encode(fn, &tm.out, d_out, 2, dims, str, box);
  }
  if (!ok) return;
  cudaFuncSetAttribute(fused_kernel, cudaFuncAttributeMaxDynamicSharedMemorySize, SMEM_BYTES);
  fused_kernel<<<NUM_CTAS, NUM_THREADS, SMEM_BYTES>>>(tm);
}
```

```cpp
#include <cuda_runtime.h>
#include <cuda_bf16.h>
#include <cuda.h>
#include <stdint.h>
#include <type_traits>

namespace {

__device__ __forceinline__ void wgmma_n192(float (&d)[128], uint64_t da, uint64_t db, int scale_d) {
  asm volatile("{\n.reg .pred p;\nsetp.ne.b32 p, %98, 0;\n"
    "wgmma.mma_async.sync.aligned.m64n192k16.f32.bf16.bf16 "
    "{%0, %1, %2, %3, %4, %5, %6, %7, %8, %9, %10, %11, %12, %13, %14, %15, "
    "%16, %17, %18, %19, %20, %21, %22, %23, %24, %25, %26, %27, %28, %29, %30, %31, "
    "%32, %33, %34, %35, %36, %37, %38, %39, %40, %41, %42, %43, %44, %45, %46, %47, "
    "%48, %49, %50, %51, %52, %53, %54, %55, %56, %57, %58, %59, %60, %61, %62, %63, "
    "%64, %65, %66, %67, %68, %69, %70, %71, %72, %73, %74, %75, %76, %77, %78, %79, "
    "%80, %81, %82, %83, %84, %85, %86, %87, %88, %89, %90, %91, %92, %93, %94, %95}, "
    "%96, %97, p, 1, 1, 0, 1;\n}\n"
    : "+f"(d[0]), "+f"(d[1]), "+f"(d[2]), "+f"(d[3]), "+f"(d[4]), "+f"(d[5]), "+f"(d[6]), "+f"(d[7]),
      "+f"(d[8]), "+f"(d[9]), "+f"(d[10]), "+f"(d[11]), "+f"(d[12]), "+f"(d[13]), "+f"(d[14]), "+f"(d[15]),
      "+f"(d[16]), "+f"(d[17]), "+f"(d[18]), "+f"(d[19]), "+f"(d[20]), "+f"(d[21]), "+f"(d[22]), "+f"(d[23]),
      "+f"(d[24]), "+f"(d[25]), "+f"(d[26]), "+f"(d[27]), "+f"(d[28]), "+f"(d[29]), "+f"(d[30]), "+f"(d[31]),
      "+f"(d[32]), "+f"(d[33]), "+f"(d[34]), "+f"(d[35]), "+f"(d[36]), "+f"(d[37]), "+f"(d[38]), "+f"(d[39]),
      "+f"(d[40]), "+f"(d[41]), "+f"(d[42]), "+f"(d[43]), "+f"(d[44]), "+f"(d[45]), "+f"(d[46]), "+f"(d[47]),
      "+f"(d[48]), "+f"(d[49]), "+f"(d[50]), "+f"(d[51]), "+f"(d[52]), "+f"(d[53]), "+f"(d[54]), "+f"(d[55]),
      "+f"(d[56]), "+f"(d[57]), "+f"(d[58]), "+f"(d[59]), "+f"(d[60]), "+f"(d[61]), "+f"(d[62]), "+f"(d[63]),
      "+f"(d[64]), "+f"(d[65]), "+f"(d[66]), "+f"(d[67]), "+f"(d[68]), "+f"(d[69]), "+f"(d[70]), "+f"(d[71]),
      "+f"(d[72]), "+f"(d[73]), "+f"(d[74]), "+f"(d[75]), "+f"(d[76]), "+f"(d[77]), "+f"(d[78]), "+f"(d[79]),
      "+f"(d[80]), "+f"(d[81]), "+f"(d[82]), "+f"(d[83]), "+f"(d[84]), "+f"(d[85]), "+f"(d[86]), "+f"(d[87]),
      "+f"(d[88]), "+f"(d[89]), "+f"(d[90]), "+f"(d[91]), "+f"(d[92]), "+f"(d[93]), "+f"(d[94]), "+f"(d[95])
    : "l"(da), "l"(db), "r"(scale_d));
}

__device__ __forceinline__ void wgmma_n256(float (&d)[128], uint64_t da, uint64_t db, int scale_d) {
  asm volatile("{\n.reg .pred p;\nsetp.ne.b32 p, %130, 0;\n"
    "wgmma.mma_async.sync.aligned.m64n256k16.f32.bf16.bf16 "
    "{%0, %1, %2, %3, %4, %5, %6, %7, %8, %9, %10, %11, %12, %13, %14, %15, "
    "%16, %17, %18, %19, %20, %21, %22, %23, %24, %25, %26, %27, %28, %29, %30, %31, "
    "%32, %33, %34, %35, %36, %37, %38, %39, %40, %41, %42, %43, %44, %45, %46, %47, "
    "%48, %49, %50, %51, %52, %53, %54, %55, %56, %57, %58, %59, %60, %61, %62, %63, "
    "%64, %65, %66, %67, %68, %69, %70, %71, %72, %73, %74, %75, %76, %77, %78, %79, "
    "%80, %81, %82, %83, %84, %85, %86, %87, %88, %89, %90, %91, %92, %93, %94, %95, "
    "%96, %97, %98, %99, %100, %101, %102, %103, %104, %105, %106, %107, %108, %109, %110, %111, "
    "%112, %113, %114, %115, %116, %117, %118, %119, %120, %121, %122, %123, %124, %125, %126, %127}, "
    "%128, %129, p, 1, 1, 0, 1;\n}\n"
    : "+f"(d[0]), "+f"(d[1]), "+f"(d[2]), "+f"(d[3]), "+f"(d[4]), "+f"(d[5]), "+f"(d[6]), "+f"(d[7]),
      "+f"(d[8]), "+f"(d[9]), "+f"(d[10]), "+f"(d[11]), "+f"(d[12]), "+f"(d[13]), "+f"(d[14]), "+f"(d[15]),
      "+f"(d[16]), "+f"(d[17]), "+f"(d[18]), "+f"(d[19]), "+f"(d[20]), "+f"(d[21]), "+f"(d[22]), "+f"(d[23]),
      "+f"(d[24]), "+f"(d[25]), "+f"(d[26]), "+f"(d[27]), "+f"(d[28]), "+f"(d[29]), "+f"(d[30]), "+f"(d[31]),
      "+f"(d[32]), "+f"(d[33]), "+f"(d[34]), "+f"(d[35]), "+f"(d[36]), "+f"(d[37]), "+f"(d[38]), "+f"(d[39]),
      "+f"(d[40]), "+f"(d[41]), "+f"(d[42]), "+f"(d[43]), "+f"(d[44]), "+f"(d[45]), "+f"(d[46]), "+f"(d[47]),
      "+f"(d[48]), "+f"(d[49]), "+f"(d[50]), "+f"(d[51]), "+f"(d[52]), "+f"(d[53]), "+f"(d[54]), "+f"(d[55]),
      "+f"(d[56]), "+f"(d[57]), "+f"(d[58]), "+f"(d[59]), "+f"(d[60]), "+f"(d[61]), "+f"(d[62]), "+f"(d[63]),
      "+f"(d[64]), "+f"(d[65]), "+f"(d[66]), "+f"(d[67]), "+f"(d[68]), "+f"(d[69]), "+f"(d[70]), "+f"(d[71]),
      "+f"(d[72]), "+f"(d[73]), "+f"(d[74]), "+f"(d[75]), "+f"(d[76]), "+f"(d[77]), "+f"(d[78]), "+f"(d[79]),
      "+f"(d[80]), "+f"(d[81]), "+f"(d[82]), "+f"(d[83]), "+f"(d[84]), "+f"(d[85]), "+f"(d[86]), "+f"(d[87]),
      "+f"(d[88]), "+f"(d[89]), "+f"(d[90]), "+f"(d[91]), "+f"(d[92]), "+f"(d[93]), "+f"(d[94]), "+f"(d[95]),
      "+f"(d[96]), "+f"(d[97]), "+f"(d[98]), "+f"(d[99]), "+f"(d[100]), "+f"(d[101]), "+f"(d[102]), "+f"(d[103]),
      "+f"(d[104]), "+f"(d[105]), "+f"(d[106]), "+f"(d[107]), "+f"(d[108]), "+f"(d[109]), "+f"(d[110]), "+f"(d[111]),
      "+f"(d[112]), "+f"(d[113]), "+f"(d[114]), "+f"(d[115]), "+f"(d[116]), "+f"(d[117]), "+f"(d[118]), "+f"(d[119]),
      "+f"(d[120]), "+f"(d[121]), "+f"(d[122]), "+f"(d[123]), "+f"(d[124]), "+f"(d[125]), "+f"(d[126]), "+f"(d[127])
    : "l"(da), "l"(db), "r"(scale_d));
}

template <int O>
__device__ __forceinline__ void wgmma_n128(float (&d)[128], uint64_t da, uint64_t db, int scale_d) {
  asm volatile("{\n.reg .pred p;\nsetp.ne.b32 p, %66, 0;\n"
    "wgmma.mma_async.sync.aligned.m64n128k16.f32.bf16.bf16 "
    "{%0, %1, %2, %3, %4, %5, %6, %7, %8, %9, %10, %11, %12, %13, %14, %15, "
    "%16, %17, %18, %19, %20, %21, %22, %23, %24, %25, %26, %27, %28, %29, %30, %31, "
    "%32, %33, %34, %35, %36, %37, %38, %39, %40, %41, %42, %43, %44, %45, %46, %47, "
    "%48, %49, %50, %51, %52, %53, %54, %55, %56, %57, %58, %59, %60, %61, %62, %63}, "
    "%64, %65, p, 1, 1, 0, 1;\n}\n"
    : "+f"(d[O + 0]), "+f"(d[O + 1]), "+f"(d[O + 2]), "+f"(d[O + 3]), "+f"(d[O + 4]), "+f"(d[O + 5]), "+f"(d[O + 6]), "+f"(d[O + 7]),
      "+f"(d[O + 8]), "+f"(d[O + 9]), "+f"(d[O + 10]), "+f"(d[O + 11]), "+f"(d[O + 12]), "+f"(d[O + 13]), "+f"(d[O + 14]), "+f"(d[O + 15]),
      "+f"(d[O + 16]), "+f"(d[O + 17]), "+f"(d[O + 18]), "+f"(d[O + 19]), "+f"(d[O + 20]), "+f"(d[O + 21]), "+f"(d[O + 22]), "+f"(d[O + 23]),
      "+f"(d[O + 24]), "+f"(d[O + 25]), "+f"(d[O + 26]), "+f"(d[O + 27]), "+f"(d[O + 28]), "+f"(d[O + 29]), "+f"(d[O + 30]), "+f"(d[O + 31]),
      "+f"(d[O + 32]), "+f"(d[O + 33]), "+f"(d[O + 34]), "+f"(d[O + 35]), "+f"(d[O + 36]), "+f"(d[O + 37]), "+f"(d[O + 38]), "+f"(d[O + 39]),
      "+f"(d[O + 40]), "+f"(d[O + 41]), "+f"(d[O + 42]), "+f"(d[O + 43]), "+f"(d[O + 44]), "+f"(d[O + 45]), "+f"(d[O + 46]), "+f"(d[O + 47]),
      "+f"(d[O + 48]), "+f"(d[O + 49]), "+f"(d[O + 50]), "+f"(d[O + 51]), "+f"(d[O + 52]), "+f"(d[O + 53]), "+f"(d[O + 54]), "+f"(d[O + 55]),
      "+f"(d[O + 56]), "+f"(d[O + 57]), "+f"(d[O + 58]), "+f"(d[O + 59]), "+f"(d[O + 60]), "+f"(d[O + 61]), "+f"(d[O + 62]), "+f"(d[O + 63])
    : "l"(da), "l"(db), "r"(scale_d));
}

template <int O>
__device__ __forceinline__ void wgmma_n128_rs(float (&d)[128], const uint32_t (&a)[4], uint64_t db) {
  asm volatile("wgmma.mma_async.sync.aligned.m64n128k16.f32.bf16.bf16 "
    "{%0, %1, %2, %3, %4, %5, %6, %7, %8, %9, %10, %11, %12, %13, %14, %15, "
    "%16, %17, %18, %19, %20, %21, %22, %23, %24, %25, %26, %27, %28, %29, %30, %31, "
    "%32, %33, %34, %35, %36, %37, %38, %39, %40, %41, %42, %43, %44, %45, %46, %47, "
    "%48, %49, %50, %51, %52, %53, %54, %55, %56, %57, %58, %59, %60, %61, %62, %63}, "
    "{%64, %65, %66, %67}, %68, 1, 1, 1, 1;\n"
    : "+f"(d[O + 0]), "+f"(d[O + 1]), "+f"(d[O + 2]), "+f"(d[O + 3]), "+f"(d[O + 4]), "+f"(d[O + 5]), "+f"(d[O + 6]), "+f"(d[O + 7]),
      "+f"(d[O + 8]), "+f"(d[O + 9]), "+f"(d[O + 10]), "+f"(d[O + 11]), "+f"(d[O + 12]), "+f"(d[O + 13]), "+f"(d[O + 14]), "+f"(d[O + 15]),
      "+f"(d[O + 16]), "+f"(d[O + 17]), "+f"(d[O + 18]), "+f"(d[O + 19]), "+f"(d[O + 20]), "+f"(d[O + 21]), "+f"(d[O + 22]), "+f"(d[O + 23]),
      "+f"(d[O + 24]), "+f"(d[O + 25]), "+f"(d[O + 26]), "+f"(d[O + 27]), "+f"(d[O + 28]), "+f"(d[O + 29]), "+f"(d[O + 30]), "+f"(d[O + 31]),
      "+f"(d[O + 32]), "+f"(d[O + 33]), "+f"(d[O + 34]), "+f"(d[O + 35]), "+f"(d[O + 36]), "+f"(d[O + 37]), "+f"(d[O + 38]), "+f"(d[O + 39]),
      "+f"(d[O + 40]), "+f"(d[O + 41]), "+f"(d[O + 42]), "+f"(d[O + 43]), "+f"(d[O + 44]), "+f"(d[O + 45]), "+f"(d[O + 46]), "+f"(d[O + 47]),
      "+f"(d[O + 48]), "+f"(d[O + 49]), "+f"(d[O + 50]), "+f"(d[O + 51]), "+f"(d[O + 52]), "+f"(d[O + 53]), "+f"(d[O + 54]), "+f"(d[O + 55]),
      "+f"(d[O + 56]), "+f"(d[O + 57]), "+f"(d[O + 58]), "+f"(d[O + 59]), "+f"(d[O + 60]), "+f"(d[O + 61]), "+f"(d[O + 62]), "+f"(d[O + 63])
    : "r"(a[0]), "r"(a[1]), "r"(a[2]), "r"(a[3]), "l"(db));
}

template <int O>
__device__ __forceinline__ void wgmma_n64_rs(float (&d)[128], const uint32_t (&a)[4], uint64_t db) {
  asm volatile("wgmma.mma_async.sync.aligned.m64n64k16.f32.bf16.bf16 "
    "{%0, %1, %2, %3, %4, %5, %6, %7, %8, %9, %10, %11, %12, %13, %14, %15, "
    "%16, %17, %18, %19, %20, %21, %22, %23, %24, %25, %26, %27, %28, %29, %30, %31}, "
    "{%32, %33, %34, %35}, %36, 1, 1, 1, 1;\n"
    : "+f"(d[O + 0]), "+f"(d[O + 1]), "+f"(d[O + 2]), "+f"(d[O + 3]), "+f"(d[O + 4]), "+f"(d[O + 5]), "+f"(d[O + 6]), "+f"(d[O + 7]),
      "+f"(d[O + 8]), "+f"(d[O + 9]), "+f"(d[O + 10]), "+f"(d[O + 11]), "+f"(d[O + 12]), "+f"(d[O + 13]), "+f"(d[O + 14]), "+f"(d[O + 15]),
      "+f"(d[O + 16]), "+f"(d[O + 17]), "+f"(d[O + 18]), "+f"(d[O + 19]), "+f"(d[O + 20]), "+f"(d[O + 21]), "+f"(d[O + 22]), "+f"(d[O + 23]),
      "+f"(d[O + 24]), "+f"(d[O + 25]), "+f"(d[O + 26]), "+f"(d[O + 27]), "+f"(d[O + 28]), "+f"(d[O + 29]), "+f"(d[O + 30]), "+f"(d[O + 31])
    : "r"(a[0]), "r"(a[1]), "r"(a[2]), "r"(a[3]), "l"(db));
}

constexpr int NUM_CTAS = 128;
constexpr int NUM_THREADS = 384;
constexpr int G1_STAGES = 5, G2_STAGES = 4;
constexpr uint32_t A_BYTES = 16384;
constexpr uint32_t G1_STAGE = 40960;
constexpr uint32_t G2_STAGE = 49152;
constexpr uint32_t RING_BYTES = G1_STAGES * G1_STAGE;
constexpr uint32_t OFF_X = RING_BYTES;
constexpr uint32_t OFF_BAR = OFF_X + 9 * 2048;
constexpr uint32_t SMEM_BYTES = OFF_BAR + 512;
constexpr uint32_t SPIN_LIMIT = 1u << 21;

struct alignas(64) TMaps {
  CUtensorMap x[2], w[2], wo[2], out;
  CUtensorMap x0[2], w0[2];
  const void* xp[2];
  const void* wp[2];
  uint32_t zero;
};

__device__ uint4 g_o[32 * 16 * 1024];
__device__ ulonglong2 g_halo[NUM_CTAS * 4 * 256];
__device__ unsigned g_o_ready[32 * 4];
__device__ unsigned g_epoch[NUM_CTAS];

__device__ __forceinline__ void mbar_init(uint32_t bar, uint32_t count) {
  asm volatile("mbarrier.init.shared::cta.b64 [%0], %1;" ::"r"(bar), "r"(count) : "memory");
}
__device__ __forceinline__ bool mbar_try_wait(uint32_t bar, uint32_t parity) {
  uint32_t ok;
  asm volatile("{\n.reg .pred p;\nmbarrier.try_wait.parity.shared::cta.b64 p, [%1], %2;\nselp.u32 %0, 1, 0, p;\n}\n"
               : "=r"(ok) : "r"(bar), "r"(parity) : "memory");
  return ok != 0;
}
__device__ __forceinline__ void mbar_wait(uint32_t bar, uint32_t parity) {
  uint32_t spins = 0;
  while (!mbar_try_wait(bar, parity)) { if (++spins > SPIN_LIMIT) __trap(); }
}
__device__ __forceinline__ void mbar_arrive(uint32_t bar) {
  asm volatile("mbarrier.arrive.shared::cta.b64 _, [%0];" ::"r"(bar) : "memory");
}
__device__ __forceinline__ void mbar_arrive_cluster(uint32_t bar_cluster_addr) {
  asm volatile("mbarrier.arrive.shared::cluster.b64 _, [%0];" ::"r"(bar_cluster_addr) : "memory");
}
__device__ __forceinline__ void mbar_expect_tx(uint32_t bar, uint32_t bytes) {
  asm volatile("mbarrier.arrive.expect_tx.shared::cta.b64 _, [%0], %1;" ::"r"(bar), "r"(bytes) : "memory");
}
__device__ __forceinline__ uint32_t mapa(uint32_t addr, uint32_t rank) {
  uint32_t r; asm("mapa.shared::cluster.u32 %0, %1, %2;" : "=r"(r) : "r"(addr), "r"(rank)); return r;
}
__device__ __forceinline__ void tma_load_2d(uint32_t dst, const CUtensorMap* m, int c0, int c1, uint32_t bar) {
  asm volatile("cp.async.bulk.tensor.2d.shared::cluster.global.mbarrier::complete_tx::bytes [%0], [%1, {%3, %4}], [%2];"
               ::"r"(dst), "l"(m), "r"(bar), "r"(c0), "r"(c1) : "memory");
}
__device__ __forceinline__ void tma_load_3d(uint32_t dst, const CUtensorMap* m, int c0, int c1, int c2, uint32_t bar) {
  asm volatile("cp.async.bulk.tensor.3d.shared::cluster.global.mbarrier::complete_tx::bytes [%0], [%1, {%3, %4, %5}], [%2];"
               ::"r"(dst), "l"(m), "r"(bar), "r"(c0), "r"(c1), "r"(c2) : "memory");
}
__device__ __forceinline__ void tma_load_3d_mc(uint32_t dst, const CUtensorMap* m, int c0, int c1, int c2, uint32_t bar, uint16_t mask) {
  asm volatile("cp.async.bulk.tensor.3d.shared::cluster.global.mbarrier::complete_tx::bytes.multicast::cluster [%0], [%1, {%3, %4, %5}], [%2], %6;"
               ::"r"(dst), "l"(m), "r"(bar), "r"(c0), "r"(c1), "r"(c2), "h"(mask) : "memory");
}
__device__ __forceinline__ void tma_store_2d(const CUtensorMap* m, int c0, int c1, uint32_t src) {
  asm volatile("cp.async.bulk.tensor.2d.global.shared::cta.bulk_group [%0, {%2, %3}], [%1];"
               ::"l"(m), "r"(src), "r"(c0), "r"(c1) : "memory");
}
__device__ __forceinline__ void bulk_load(uint32_t dst, const void* src, uint32_t bytes, uint32_t bar) {
  asm volatile("cp.async.bulk.shared::cluster.global.mbarrier::complete_tx::bytes [%0], [%1], %2, [%3];"
               ::"r"(dst), "l"(src), "r"(bytes), "r"(bar) : "memory");
}
__device__ __forceinline__ void bulk_store(void* dst, uint32_t src, uint32_t bytes) {
  asm volatile("cp.async.bulk.global.shared::cta.bulk_group [%0], [%1], %2;" ::"l"(dst), "r"(src), "r"(bytes) : "memory");
}
__device__ __forceinline__ void bulk_commit() { asm volatile("cp.async.bulk.commit_group;" ::: "memory"); }
__device__ __forceinline__ void bulk_wait0() { asm volatile("cp.async.bulk.wait_group 0;" ::: "memory"); }
__device__ __forceinline__ void bulk_wait0_read() { asm volatile("cp.async.bulk.wait_group.read 0;" ::: "memory"); }
__device__ __forceinline__ void fence_async_smem() { asm volatile("fence.proxy.async.shared::cta;" ::: "memory"); }
__device__ __forceinline__ void prefetch_tmap(const CUtensorMap* m) {
  asm volatile("prefetch.tensormap [%0];" ::"l"(m) : "memory");
}
__device__ __forceinline__ void wgmma_fence() { asm volatile("wgmma.fence.sync.aligned;" ::: "memory"); }
__device__ __forceinline__ void wgmma_commit() { asm volatile("wgmma.commit_group.sync.aligned;" ::: "memory"); }
template <int N> __device__ __forceinline__ void wgmma_wait() { asm volatile("wgmma.wait_group.sync.aligned %0;" ::"n"(N) : "memory"); }
template <int B, int N> __device__ __forceinline__ void fence_acc(float (&d)[128]) {
#pragma unroll
  for (int i = B; i < N; i++) asm volatile("" : "+f"(d[i])::"memory");
}
__device__ __forceinline__ void bar_sync(int id) { asm volatile("bar.sync %0, 256;" ::"r"(id) : "memory"); }
__device__ __forceinline__ void bar_arrive(int id) { asm volatile("bar.arrive %0, 256;" ::"r"(id) : "memory"); }
__device__ __forceinline__ void sched_fence(uint32_t zero) {
  asm volatile("{\n.reg .pred p;\nsetp.ne.u32 p, %0, 0;\n@p trap;\n}\n" ::"r"(zero) : "memory");
}
__device__ __forceinline__ uint64_t desc_kmajor(uint32_t addr) {
  return (uint64_t)((addr & 0x3FFFF) >> 4) | (1ull << 16) | (64ull << 32) | (1ull << 62);
}
__device__ __forceinline__ uint64_t desc_mnmajor(uint32_t addr) {
  return (uint64_t)((addr & 0x3FFFF) >> 4) | (256ull << 16) | (64ull << 32) | (1ull << 62);
}
__device__ __forceinline__ uint32_t pack_bf16(float lo, float hi) {
  uint32_t r; asm("cvt.rn.bf16x2.f32 %0, %1, %2;" : "=r"(r) : "f"(hi), "f"(lo)); return r;
}
__device__ __forceinline__ void stsm_x4(uint32_t addr, uint32_t r0, uint32_t r1, uint32_t r2, uint32_t r3) {
  asm volatile("stmatrix.sync.aligned.m8n8.x4.shared.b16 [%0], {%1, %2, %3, %4};" ::"r"(addr), "r"(r0), "r"(r1), "r"(r2), "r"(r3) : "memory");
}
__device__ __forceinline__ void stsm_x4_t(uint32_t addr, uint32_t r0, uint32_t r1, uint32_t r2, uint32_t r3) {
  asm volatile("stmatrix.sync.aligned.m8n8.x4.trans.shared.b16 [%0], {%1, %2, %3, %4};" ::"r"(addr), "r"(r0), "r"(r1), "r"(r2), "r"(r3) : "memory");
}
__device__ __forceinline__ void ldsm_x4(uint32_t addr, uint32_t (&r)[4]) {
  asm volatile("ldmatrix.sync.aligned.m8n8.x4.shared.b16 {%0, %1, %2, %3}, [%4];" : "=r"(r[0]), "=r"(r[1]), "=r"(r[2]), "=r"(r[3]) : "r"(addr) : "memory");
}
__device__ __forceinline__ uint32_t movm_t(uint32_t a) {
  uint32_t d; asm volatile("movmatrix.sync.aligned.m8n8.trans.b16 %0, %1;" : "=r"(d) : "r"(a)); return d;
}
__device__ __forceinline__ void mma_init(float (&c)[4], uint32_t a0, uint32_t a1, uint32_t a2, uint32_t a3, uint32_t b0, uint32_t b1) {
  asm volatile("mma.sync.aligned.m16n8k16.row.col.f32.bf16.bf16.f32 {%0, %1, %2, %3}, {%4, %5, %6, %7}, {%8, %9}, {%10, %10, %10, %10};"
               : "=f"(c[0]), "=f"(c[1]), "=f"(c[2]), "=f"(c[3]) : "r"(a0), "r"(a1), "r"(a2), "r"(a3), "r"(b0), "r"(b1), "f"(0.f));
}
__device__ __forceinline__ void mma_acc(float (&c)[4], uint32_t a0, uint32_t a1, uint32_t a2, uint32_t a3, uint32_t b0, uint32_t b1) {
  asm volatile("mma.sync.aligned.m16n8k16.row.col.f32.bf16.bf16.f32 {%0, %1, %2, %3}, {%4, %5, %6, %7}, {%8, %9}, {%0, %1, %2, %3};"
               : "+f"(c[0]), "+f"(c[1]), "+f"(c[2]), "+f"(c[3]) : "r"(a0), "r"(a1), "r"(a2), "r"(a3), "r"(b0), "r"(b1));
}
__device__ __forceinline__ float ex2(float x) { float y; asm("ex2.approx.ftz.f32 %0, %1;" : "=f"(y) : "f"(x)); return y; }
__device__ __forceinline__ unsigned ld_acquire(const unsigned* p) {
  unsigned v; asm volatile("ld.acquire.gpu.global.u32 %0, [%1];" : "=r"(v) : "l"(p) : "memory"); return v;
}
__device__ __forceinline__ void wait_flag(const unsigned* p, unsigned target) {
  uint32_t spins = 0;
  while ((int)(ld_acquire(p) - target) < 0) { if (++spins > SPIN_LIMIT) __trap(); __nanosleep(20); }
}
__device__ __forceinline__ uint4 lds128(uint32_t addr) {
  uint4 v; asm volatile("ld.shared.v4.u32 {%0, %1, %2, %3}, [%4];" : "=r"(v.x), "=r"(v.y), "=r"(v.z), "=r"(v.w) : "r"(addr) : "memory"); return v;
}
__device__ __forceinline__ void sts128(uint32_t addr, uint32_t a, uint32_t b, uint32_t c, uint32_t d) {
  asm volatile("st.shared.v4.u32 [%0], {%1, %2, %3, %4};" ::"r"(addr), "r"(a), "r"(b), "r"(c), "r"(d) : "memory");
}

template <int N>
__device__ __forceinline__ void softmax_exp(const uint32_t (&qk)[N], float (&ex)[N][2]) {
  constexpr float kScale = 0.17677669529663687f, kLog2e = 1.4426950408889634f;
  float m[N];
#pragma unroll
  for (int i = 0; i < N; i++) {
    const uint32_t p = pack_bf16(__uint_as_float(qk[i] << 16) * kScale, __uint_as_float(qk[i] & 0xffff0000u) * kScale);
    ex[i][0] = __uint_as_float(p << 16);
    ex[i][1] = __uint_as_float(p & 0xffff0000u);
    m[i] = fmaxf(ex[i][0], ex[i][1]);
  }
#pragma unroll
  for (int i = 0; i < N; i++) m[i] = fmaxf(m[i], __shfl_xor_sync(0xffffffffu, m[i], 1));
#pragma unroll
  for (int i = 0; i < N; i++) m[i] = fmaxf(m[i], __shfl_xor_sync(0xffffffffu, m[i], 2));
#pragma unroll
  for (int i = 0; i < N; i++) { ex[i][0] = ex2((ex[i][0] - m[i]) * kLog2e); ex[i][1] = ex2((ex[i][1] - m[i]) * kLog2e); }
}
template <int N>
__device__ __forceinline__ void softmax_norm(const float (&ex)[N][2], uint32_t lo_mask, uint32_t (&b_lo)[N], uint32_t (&b_hi)[N]) {
  float s[N];
#pragma unroll
  for (int i = 0; i < N; i++) s[i] = ex[i][0] + ex[i][1];
#pragma unroll
  for (int i = 0; i < N; i++) s[i] += __shfl_xor_sync(0xffffffffu, s[i], 1);
#pragma unroll
  for (int i = 0; i < N; i++) s[i] += __shfl_xor_sync(0xffffffffu, s[i], 2);
#pragma unroll
  for (int i = 0; i < N; i++) {
    float r;
    asm("rcp.approx.ftz.f32 %0, %1;" : "=f"(r) : "f"(s[i]));
    const uint32_t p = pack_bf16(ex[i][0] * r, ex[i][1] * r);
    b_lo[i] = p & lo_mask;
    b_hi[i] = p & ~lo_mask;
  }
}

__global__ void __cluster_dims__(2, 1, 1) __launch_bounds__(NUM_THREADS, 1)
fused_kernel(const __grid_constant__ TMaps tm) {
  extern __shared__ __align__(1024) uint8_t smem_raw[];
  const uint32_t sb = (uint32_t)__cvta_generic_to_shared(smem_raw);
  const int warp = __shfl_sync(0xffffffffu, threadIdx.x >> 5, 0), lane = threadIdx.x & 31;
  const int e = blockIdx.x & 1;
  int cg, rb, br;
  {
    const int c = blockIdx.x >> 1;
    int q, i;
    if (c < 4) { q = 0; i = c; }
    else if (c < 36) { q = 1 + ((c - 4) & 7); i = (c - 4) >> 3; }
    else { q = 9 + (c - 36) % 7; i = (c - 36) / 7; }
    cg = i; rb = q & 7; br = q >> 3;
  }
  const int cta = e + 2 * cg + 8 * rb + 64 * br;
  const uint32_t bar_full1 = sb + OFF_BAR, bar_empty1 = bar_full1 + 64, bar_full2 = bar_full1 + 128,
                 bar_empty2 = bar_full1 + 160, bar_o_full = bar_full1 + 192, bar_o_empty = bar_full1 + 200,
                 bar_o = bar_full1 + 208  , bar_x = bar_full1 + 240  ;

  if (warp == 8 && lane == 0) {
    prefetch_tmap(&tm.x0[br]); prefetch_tmap(&tm.w0[br]);
    prefetch_tmap(&tm.x[br]); prefetch_tmap(&tm.w[br]);
    for (int s = 0; s < G1_STAGES; s++) mbar_init(bar_full1 + 8 * s, 1);
    asm volatile("fence.mbarrier_init.release.cluster;" ::: "memory");
  } else if (warp == 9 && lane == 0) {
    for (int s = 0; s < G1_STAGES; s++) mbar_init(bar_empty1 + 8 * s, 16);
    for (int s = 0; s < G2_STAGES; s++) { mbar_init(bar_full2 + 8 * s, 1); mbar_init(bar_empty2 + 8 * s, 16); }
    for (int s = 0; s < 18; s++) mbar_init(bar_x + 8 * s, 1);
    mbar_init(bar_o_full, 8); mbar_init(bar_o_empty, 3);
    for (int t = 0; t < 4; t++) mbar_init(bar_o + 8 * t, 1);
    asm volatile("fence.mbarrier_init.release.cluster;" ::: "memory");
  } else if (warp < 2) {
    if (warp == 0) {
      const char* p = (const char*)tm.xp[br] + (size_t)(rb * 128 + cg * 32 + lane) * 4096 + e * 2048;
      asm volatile("prefetch.global.L2 [%0];" ::"l"(p));
    } else if (lane < 12) {
      const int l = rb * 2 + e + 16 * lane;
      const char* p = (const char*)tm.wp[br] + (size_t)(l / 3) * 6144 + (l % 3) * 2048 + cg * 512;
      asm volatile("prefetch.global.L2 [%0];" ::"l"(p));
    }
  }
  __syncwarp();
  asm volatile("barrier.cluster.arrive.relaxed.aligned;" ::: "memory");

  if (warp < 8) {
    asm volatile("setmaxnreg.inc.sync.aligned.u32 232;");
    asm volatile("barrier.cluster.wait.aligned;" ::: "memory");
    const int wg = warp >> 2;
    float acc[128], acc2[128];
    uint32_t pk[48];
    uint32_t kq[16], vq[16];
    float sf[8][4], of[8][4];
    float pe[4][2];
    uint32_t b_lo[4], b_hi[4];
    const bool rel_any = lane < 2;
    const uint32_t rel_base = mapa(bar_full1, lane == 0 ? e : (e ^ 1));
    const int g = lane >> 2, tq = lane & 3;
    const uint32_t lo_mask = (2 * tq > g ? 0xffffu : 0u) | (2 * tq + 1 > g ? 0xffff0000u : 0u);
    const bool seq_start = (rb == 0 && warp == 0);
    const uint32_t slot = sb + OFF_X + warp * 2048;
    int s = 1, ph = 0;

    enum { XK = 1, MH = 2, XV = 4, ML = 8, RK = 16, S1 = 32, S2 = 64, RV = 128, ST0 = 256, ST1 = 512, QK = 1024, PV = 2048 };
    auto attn = [&](auto phase, int ta) __attribute__((always_inline)) {
      constexpr int P = decltype(phase)::value;
      if constexpr ((P & XK) != 0) {
        if (ta > 0) mbar_wait(bar_o_empty, (ta - 1) & 1);
        sts128(slot + 2048 + lane * 16, pk[17] ^ tm.zero, pk[19] ^ tm.zero, pk[21] ^ tm.zero, pk[23] ^ tm.zero);
        sts128(slot + 2560 + lane * 16, pk[25] ^ tm.zero, pk[27] ^ tm.zero, pk[29] ^ tm.zero, pk[31] ^ tm.zero);
        __syncwarp();
        if (lane == 0) mbar_arrive(bar_x + 16 * warp + 16);
      }
      if constexpr ((P & MH) != 0) {
#pragma unroll
        for (int i = 1; i < 16; i += 2) pk[32 + i] = movm_t(pk[32 + i]);
      }
      if constexpr ((P & XV) != 0) {
        sts128(slot + 3072 + lane * 16, pk[33] ^ tm.zero, pk[35] ^ tm.zero, pk[37] ^ tm.zero, pk[39] ^ tm.zero);
        sts128(slot + 3584 + lane * 16, pk[41] ^ tm.zero, pk[43] ^ tm.zero, pk[45] ^ tm.zero, pk[47] ^ tm.zero);
        __syncwarp();
        if (lane == 0) mbar_arrive(bar_x + 16 * warp + 24);
      }
      if constexpr ((P & ML) != 0) {
#pragma unroll
        for (int i = 0; i < 16; i += 2) pk[32 + i] = movm_t(pk[32 + i]);
      }
      if constexpr ((P & S1) != 0) {
        if (seq_start) sf[0][0] = sf[0][1] = sf[2][0] = sf[2][1] = -INFINITY;
        uint32_t qk[4];
#pragma unroll
        for (int i = 0; i < 4; i++) qk[i] = movm_t(pack_bf16(g > 2 * tq ? sf[i][0] : sf[i][2], g > 2 * tq + 1 ? sf[i][1] : sf[i][3]));
        softmax_exp<4>(qk, pe);
      }
      if constexpr ((P & S2) != 0) softmax_norm<4>(pe, lo_mask, b_lo, b_hi);
      if constexpr ((P & (RK | RV)) != 0) {
        constexpr int V = (P & RV) != 0;
#pragma unroll
        for (int i = 0; i < (V ? 32 : 16); i++) (V ? of : sf)[i / 4][i % 4] = 0.f;
        mbar_wait(bar_x + 16 * warp + 8 * V, ta & 1);
        const uint4 x0 = lds128(slot + V * 1024 + lane * 16), x1 = lds128(slot + V * 1024 + 512 + lane * 16);
        const uint32_t xx[8] = {x0.x, x0.y, x0.z, x0.w, x1.x, x1.y, x1.z, x1.w};
#pragma unroll
        for (int i = 0; i < 8; i++) {
          if constexpr (V) { vq[(i / 2) * 4 + (i & 1)] = xx[i] ^ tm.zero; vq[(i / 2) * 4 + 2 + (i & 1)] = pk[32 + 2 * i] ^ tm.zero; }
          else { kq[2 * i] = xx[i] ^ tm.zero; kq[2 * i + 1] = pk[16 + 2 * i] ^ tm.zero; }
        }
      }
      if constexpr ((P & (ST0 | ST1)) != 0) {
#pragma unroll
        for (int i = (P & ST0) ? 0 : 2; i < ((P & ST1) ? 4 : 2); i++)
          stsm_x4_t(slot + ((i & 1) * 8 + (lane & 7)) * 128 + ((((i >> 1) * 4 + (lane >> 3)) ^ (lane & 7)) << 4),
                    pack_bf16(of[2 * i][0], of[2 * i][1]), pack_bf16(of[2 * i][2], of[2 * i][3]),
                    pack_bf16(of[2 * i + 1][0], of[2 * i + 1][1]), pack_bf16(of[2 * i + 1][2], of[2 * i + 1][3]));
        if constexpr ((P & ST1) != 0) {
          fence_async_smem();
          __syncwarp();
          if (lane == 0) mbar_arrive(bar_o_full);
        }
      }
    };
    auto burst = [&](auto phase, auto from, auto to) __attribute__((always_inline)) {
      constexpr int P = decltype(phase)::value, B = decltype(from)::value, E = decltype(to)::value;
#pragma unroll
      for (int n = B; n < E; n++) {
        if constexpr (P == QK) {
          const int k = n / 4, h = (n / 2) & 1, hf = n & 1, q = 8 * h + 4 * k;
          const uint32_t* a = hf ? &pk[16 + q] : &kq[q];
          if (k == 0) mma_init(sf[2 * h + hf], a[0], a[1], a[2], a[3], pk[q + hf], pk[q + 2 + hf]);
          else mma_acc(sf[2 * h + hf], a[0], a[1], a[2], a[3], pk[q + hf], pk[q + 2 + hf]);
        } else {
          const int h = n / 4, hf = (n / 2) & 1, v = 8 * h + 4 * (n & 1);
          if (hf == 0) mma_init(of[n], vq[v], vq[v + 1], vq[v + 2], vq[v + 3], b_lo[2 * h], b_hi[2 * h]);
          else mma_init(of[n], pk[32 + v], pk[34 + v], pk[33 + v], pk[35 + v], b_lo[2 * h + 1], b_hi[2 * h + 1]);
        }
      }
    };
#define PH(n) std::integral_constant<int, n>{}
    uint32_t rel = 0;
    uint64_t da_next = desc_kmajor(sb + G1_STAGE + wg * 8192), db_next = desc_mnmajor(sb + G1_STAGE + A_BYTES);
    auto kstep = [&](auto g2, auto pre0, auto post, auto burst1, bool first, int ta, bool next_g2) __attribute__((always_inline)) {
      constexpr bool G2 = decltype(g2)::value;
      constexpr uint64_t HALF = G2 ? 1024 : 768;
      const uint64_t da = da_next, db = db_next;
      if constexpr (decltype(pre0)::value != 0) { if (wg == 0) burst(pre0, PH(0), PH(8)); }
      bar_sync(1 + wg);
      wgmma_fence();
      if constexpr (G2) {
        wgmma_n256(acc2, da, db, !first);
        wgmma_n256(acc2, da + 2, db + 128, 1);
        wgmma_n256(acc2, da + 4, db + HALF, 1);
        wgmma_n256(acc2, da + 6, db + HALF + 128, 1);
      } else {
        wgmma_n192(acc, da, db, !first);
        wgmma_n192(acc, da + 2, db + 128, 1);
        wgmma_n192(acc, da + 4, db + HALF, 1);
        wgmma_n192(acc, da + 6, db + HALF + 128, 1);
      }
      wgmma_commit();
      const bool late = decltype(burst1)::value != 0 && wg == 1;
      if (!late) bar_arrive(2 - wg);
      if (rel) mbar_arrive_cluster(rel);
      rel = rel_any ? rel_base + (G2 ? 160 : 64) + 8 * s : 0;
      if constexpr (decltype(post)::value != 0) {
        sched_fence(tm.zero);
        attn(post, ta);
      }
      if (++s == (G2 ? G2_STAGES : G1_STAGES)) s = 0;
      if (s == (G2 ? 0 : 1)) ph ^= 1;
      if (!G2 && next_g2) { s = 0; ph = 0; }
      {
        const uint32_t st = sb + s * (next_g2 ? G2_STAGE : G1_STAGE);
        uint32_t a_lo = (uint32_t)desc_kmajor(st + wg * 8192), b_lo = (uint32_t)desc_mnmajor(st + A_BYTES);
        asm volatile("" : "+r"(a_lo), "+r"(b_lo));
        da_next = (desc_kmajor(0) & ~0xffffffffull) | a_lo;
        db_next = (desc_mnmajor(0) & ~0xffffffffull) | b_lo;
      }
      mbar_wait((next_g2 ? bar_full2 : bar_full1) + 8 * s, ph);
      if constexpr (decltype(burst1)::value != 0) {
        if (late) {
          constexpr int N = 8, M = decltype(burst1)::value == QK ? 5 : 4;
          burst(burst1, PH(0), PH(N - M));
          sched_fence(tm.zero);
          bar_arrive(1);
          burst(burst1, PH(N - M), PH(N));
        }
      }
      wgmma_wait<0>();
    };
    using F = std::false_type; using T = std::true_type;
    if (wg == 1) bar_arrive(1);
    mbar_wait(bar_full1 + 8 * s, ph);

    constexpr int sc1[11] = {0, XK, MH, XV, ML, RK | QK, S1, S2, RV | PV, ST0, ST1};
    constexpr int sc2[7] = {0, XK | MH, XV, ML, RK | QK, S1 | S2 | RV | PV, ST0 | ST1};
#define KSTEP(g2, sc, i, ta, next) \
    kstep(g2, PH(sc[i] & (QK | PV)), PH(sc[i + 1] & ~(QK | PV)), PH(sc[i + 1] & (QK | PV)), i == 0, ta, next)
    kstep(F{}, PH(0), PH(0), PH(0), true, 0, false);
#pragma unroll 1
    for (int ks = 1; ks < 10; ks++) kstep(F{}, PH(0), PH(0), PH(0), false, 0, false);
#pragma unroll 1
    for (int t = 0;; t++) {
#pragma unroll 1
      for (int ks = 10; ks < 16; ks++) kstep(F{}, PH(0), PH(0), PH(0), false, 0, t == 3 && ks == 15);
      fence_acc<0, 96>(acc);
#pragma unroll
      for (int i = 0; i < 48; i++) pk[i] = pack_bf16(acc[2 * i], acc[2 * i + 1]);
      if (t == 3) break;
      KSTEP(F{}, sc1, 0, t, 0);  KSTEP(F{}, sc1, 1, t, 0); KSTEP(F{}, sc1, 2, t, 0);
      KSTEP(F{}, sc1, 3, t, 0); KSTEP(F{}, sc1, 4, t, 0); KSTEP(F{}, sc1, 5, t, 0);
      KSTEP(F{}, sc1, 6, t, 0); KSTEP(F{}, sc1, 7, t, 0); KSTEP(F{}, sc1, 8, t, 0);
      KSTEP(F{}, sc1, 9, t, 0);
    }
    KSTEP(T{}, sc2, 0, 3, 1);  KSTEP(T{}, sc2, 1, 3, 1); KSTEP(T{}, sc2, 2, 3, 1);
    KSTEP(T{}, sc2, 3, 3, 1); KSTEP(T{}, sc2, 4, 3, 1); KSTEP(T{}, sc2, 5, 3, 1);
#pragma unroll 1
    for (int ks = 6; ks < 12; ks++) kstep(T{}, PH(0), PH(0), PH(0), false, 0, true);
    if (rel) mbar_arrive_cluster(rel);
    auto store_chunk = [&](auto chunk, float (&ac)[128]) __attribute__((always_inline)) {
      constexpr int c = decltype(chunk)::value;
      const uint32_t stg = sb + c * G2_STAGE + warp * 2048;
      const int r = ((lane >> 3) & 1) * 8 + (lane & 7);
#pragma unroll
      for (int jj = 0; jj < 8; jj += 2) {
        const int j = c * 8 + jj;
        stsm_x4(stg + r * 128 + (((jj + (lane >> 4)) ^ (r & 7)) << 4), pack_bf16(ac[4 * j], ac[4 * j + 1]),
                pack_bf16(ac[4 * j + 2], ac[4 * j + 3]), pack_bf16(ac[4 * j + 4], ac[4 * j + 5]),
                pack_bf16(ac[4 * j + 6], ac[4 * j + 7]));
      }
      fence_async_smem();
      __syncwarp();
      if (lane == 0) {
        tma_store_2d(&tm.out, e * 2048 + br * 1024 + cg * 256 + c * 64, rb * 128 + warp * 16, stg);
        bulk_commit();
      }
    };
    if (wg == 0) {
      float acc3[128];
#pragma unroll
      for (int i = 0; i < 128; i++) asm volatile("mov.b32 %0, %1;" : "=f"(acc3[i]) : "f"(acc2[i]));
      auto half_step = [&](auto side, int j) __attribute__((always_inline)) {
        constexpr int R = decltype(side)::value;
        const uint64_t da = desc_kmajor(sb + j * G2_STAGE);
        const uint64_t db = desc_mnmajor(sb + j * G2_STAGE + A_BYTES) + R * 512;
        wgmma_n128<R * 64>(acc3, da, db, 1);
        wgmma_n128<R * 64>(acc3, da + 2, db + 128, 1);
        wgmma_n128<R * 64>(acc3, da + 4, db + 1024, 1);
        wgmma_n128<R * 64>(acc3, da + 6, db + 1024 + 128, 1);
      };
      bar_sync(1);
#pragma unroll 1
      for (int j = 0; j < 2; j++) { mbar_wait(bar_full2 + 8 * j, 1); wgmma_fence(); half_step(PH(0), j); half_step(PH(1), j); wgmma_commit(); }
#pragma unroll 1
      for (int j = 2; j < 4; j++) { mbar_wait(bar_full2 + 8 * j, 1); wgmma_fence(); half_step(PH(0), j); wgmma_commit(); }
      wgmma_fence();
      half_step(PH(1), 2); half_step(PH(1), 3);
      wgmma_commit();
      bar_arrive(2);
      wgmma_wait<1>();
      fence_acc<0, 64>(acc3);
      store_chunk(PH(0), acc3); store_chunk(PH(1), acc3);
      wgmma_wait<0>();
      fence_acc<64, 128>(acc3);
      store_chunk(PH(2), acc3); store_chunk(PH(3), acc3);
    } else {
      float acc3[128];
#pragma unroll
      for (int i = 0; i < 128; i++) asm volatile("mov.b32 %0, %1;" : "=f"(acc3[i]) : "f"(acc2[i]));
      uint32_t af[16][4];
      const int r = ((lane >> 3) & 1) * 8 + (lane & 7);
#pragma unroll
      for (int j = 0; j < 4; j++) {
        mbar_wait(bar_full2 + 8 * j, 1);
#pragma unroll
        for (int k = 0; k < 4; k++) ldsm_x4(sb + j * G2_STAGE + warp * 2048 + r * 128 + (((2 * k + (lane >> 4)) ^ (r & 7)) << 4), af[4 * j + k]);
      }
      bar_sync(2);
      wgmma_fence();
      const uint64_t db = desc_mnmajor(sb + A_BYTES);
#define B_OFF(i) (((i) >> 2) * (G2_STAGE >> 4) + (((i) >> 1) & 1) * 1024 + ((i) & 1) * 128)
#pragma unroll
      for (int i = 0; i < 16; i++) wgmma_n128_rs<0>(acc3, af[i], db + B_OFF(i));
      wgmma_commit();
#pragma unroll
      for (int i = 0; i < 16; i++) wgmma_n64_rs<64>(acc3, af[i], db + B_OFF(i) + 512);
      wgmma_commit();
      wgmma_wait<1>();
      fence_acc<0, 64>(acc3);
      store_chunk(PH(0), acc3);
      wgmma_fence();
#pragma unroll
      for (int i = 0; i < 16; i++) wgmma_n64_rs<96>(acc3, af[i], db + B_OFF(i) + 768);
      wgmma_commit();
      store_chunk(PH(1), acc3);
      wgmma_wait<1>();
      fence_acc<64, 96>(acc3);
      store_chunk(PH(2), acc3);
      wgmma_wait<0>();
      fence_acc<96, 128>(acc3);
      store_chunk(PH(3), acc3);
    }
    if (lane == 0) bulk_wait0_read();
    if (threadIdx.x == 0) { atomicAdd(&g_epoch[cta], 1u); }
  } else {
    asm volatile("setmaxnreg.dec.sync.aligned.u32 40;");
    if (warp == 8 && lane == 0) {
      fence_async_smem();
      for (int it = 0; it < G1_STAGES; it++) {
        const int s = (it + 1) % G1_STAGES;
        const uint32_t st = sb + s * G1_STAGE, fb = bar_full1 + 8 * s;
        if (it > 0) { const long long c0 = clock64(); while (clock64() - c0 < 400) {} }
        mbar_expect_tx(fb, G1_STAGE);
        tma_load_2d(st, it < 4 ? &tm.x0[br] : &tm.x[br], e * 1024 + it * 64, rb * 128, fb);
        tma_load_3d(st + A_BYTES, &tm.w0[br], cg * 256, it * 64, 0, fb);
        tma_load_3d(st + A_BYTES + 12288, &tm.w0[br], cg * 256, it * 64 + 32, 0, fb);
      }
    }
    __syncwarp();
    asm volatile("barrier.cluster.wait.aligned;" ::: "memory");
    if (warp == 8) {
      if (lane == 0) {
        int s = 1, ph = 0;
        for (int it = G1_STAGES; it < 64; it++) {
          const int ks = it & 15, hp = cg * 4 + (it >> 4);
          const uint32_t st = sb + s * G1_STAGE, fb = bar_full1 + 8 * s;
          mbar_wait(bar_empty1 + 8 * s, ph);
          mbar_expect_tx(fb, G1_STAGE);
          tma_load_2d(st, &tm.x[br], e * 1024 + ks * 64, rb * 128, fb);
          tma_load_3d_mc(st + A_BYTES + e * 12288, &tm.w[br], hp * 64, ks * 64 + e * 32, 0, fb, (uint16_t)3);
          if (it == 8) { prefetch_tmap(&tm.wo[br]); prefetch_tmap(&tm.out); }
          if (++s == G1_STAGES) s = 0;
          if (s == 1) ph ^= 1;
        }
        for (int it = 0; it < 16; it++) {
          const int kb = (it & 3) * 4 + (it >> 2), s2 = it & 3;
          const uint32_t st = sb + s2 * G2_STAGE, fb = bar_full2 + 8 * s2;
          if (it < G2_STAGES) {
            if (it == 0) mbar_wait(bar_empty1, 1);
            mbar_wait(bar_empty1 + 8 * (it + 1), 0);
          } else {
            mbar_wait(bar_empty2 + 8 * s2, ((it >> 2) - 1) & 1);
          }
          mbar_expect_tx(fb, G2_STAGE);
          tma_load_3d_mc(st + A_BYTES + e * 16384, &tm.wo[br], 0, kb * 64 + e * 32, cg * 4, fb, (uint16_t)3);
          if ((it & 3) == 0) mbar_wait(bar_o + 8 * (it >> 2), 0);
          bulk_load(st, g_o + (((br * 8 + rb) * 2 + e) * 16 + kb) * 1024, A_BYTES, fb);
        }
      }
    } else {
      const unsigned tag = __ldcg(&g_epoch[cta]) + 1u;
      if (warp < 11) {
        const int half = warp - 9;
        ulonglong2* dst = g_halo + (cta + 8) * 4 * 256 + half * 128 + lane;
        const ulonglong2* src = g_halo + cta * 4 * 256 + half * 128 + lane;
        if (rb < 7) {
          mbar_wait(bar_empty1 + 32, 0);
          const unsigned long long inv = (unsigned long long)(tag - 1u) << 32;
#pragma unroll 1
          for (int t = 0; t < 4; t++) {
#pragma unroll
            for (int p = 0; p < 4; p++)
              asm volatile("st.relaxed.gpu.global.v2.b64 [%0], {%1, %1};" ::"l"(dst + t * 256 + p * 32), "l"(inv) : "memory");
            __nanosleep(500);
          }
        }
#pragma unroll 1
        for (int t = 0; t < 4; t++) {
          mbar_wait(bar_x + 128 + 8 * half, t & 1);
          if (rb < 7) {
            const unsigned long long hi = (unsigned long long)tag << 32;
#pragma unroll
            for (int i = 0; i < 2; i++) {
              const uint4 v = lds128(sb + OFF_X + 8 * 2048 + half * 1024 + i * 512 + lane * 16);
              asm volatile("st.relaxed.gpu.global.v2.b64 [%0], {%1, %2};" ::"l"(dst + t * 256 + i * 64), "l"(hi | v.x), "l"(hi | v.y) : "memory");
              asm volatile("st.relaxed.gpu.global.v2.b64 [%0], {%1, %2};" ::"l"(dst + t * 256 + i * 64 + 32), "l"(hi | v.z), "l"(hi | v.w) : "memory");
            }
          }
          __syncwarp();
          if (lane == 0) mbar_arrive(bar_o_empty);
          unsigned long long v[8];
          if (rb > 0) {
            uint32_t spins = 0;
            while (true) {
#pragma unroll
              for (int p = 0; p < 4; p++)
                asm volatile("ld.relaxed.gpu.global.v2.b64 {%0, %1}, [%2];" : "=l"(v[2 * p]), "=l"(v[2 * p + 1])
                             : "l"(src + t * 256 + p * 32) : "memory");
              bool ok = true;
#pragma unroll
              for (int p = 0; p < 8; p++) ok &= (unsigned)(v[p] >> 32) == tag;
              if (__all_sync(0xffffffffu, ok)) break;
              if (++spins > SPIN_LIMIT) __trap();
            }
          } else {
#pragma unroll
            for (int p = 0; p < 8; p++) v[p] = 0;
          }
#pragma unroll
          for (int i = 0; i < 2; i++)
            sts128(sb + OFF_X + half * 1024 + i * 512 + lane * 16, (uint32_t)v[4 * i], (uint32_t)v[4 * i + 1], (uint32_t)v[4 * i + 2], (uint32_t)v[4 * i + 3]);
          __syncwarp();
          if (lane == 0) { mbar_arrive(bar_x + 8 * half); }
        }
      } else if (lane == 0) {
        unsigned* flag = &g_o_ready[((br * 8 + rb) * 2 + e) * 4];
        uint4* dst = g_o + (((br * 8 + rb) * 2 + e) * 16 + cg * 4) * 1024;
#pragma unroll 1
        for (int t = 0; t < 4; t++, flag++) {
          mbar_wait(bar_o_full, t & 1);
#pragma unroll 1
          for (int i = 0; i < 8; i++, dst += 128) {
            bulk_store(dst, sb + OFF_X + i * 2048, 2048);
            if (i < 7) __nanosleep(t < 3 ? 80 : 50);
          }
          bulk_commit();
          bulk_wait0_read();
          mbar_arrive(bar_o_empty);
          bulk_wait0();
          asm volatile("red.release.gpu.global.add.u32 [%0], 1;" ::"l"(flag) : "memory");
          wait_flag(flag, tag * 4u);
          asm volatile("fence.proxy.async.global;" ::: "memory");
          mbar_arrive(bar_o + 8 * t);
        }
      }
    }
  }
}

typedef CUresult (*EncodeFn)(CUtensorMap*, CUtensorMapDataType, cuuint32_t, void*, const cuuint64_t*, const cuuint64_t*,
                             const cuuint32_t*, const cuuint32_t*, CUtensorMapInterleave, CUtensorMapSwizzle,
                             CUtensorMapL2promotion, CUtensorMapFloatOOBfill);

bool encode(EncodeFn fn, CUtensorMap* m, const void* ptr, int rank, const cuuint64_t* dims, const cuuint64_t* strides,
            const cuuint32_t* box, CUtensorMapL2promotion promo = CU_TENSOR_MAP_L2_PROMOTION_L2_256B) {
  const cuuint32_t es[3] = {1, 1, 1};
  return fn(m, CU_TENSOR_MAP_DATA_TYPE_BFLOAT16, rank, const_cast<void*>(ptr), dims, strides, box, es,
            CU_TENSOR_MAP_INTERLEAVE_NONE, CU_TENSOR_MAP_SWIZZLE_128B, promo,
            CU_TENSOR_MAP_FLOAT_OOB_FILL_NONE) == CUDA_SUCCESS;
}

}

extern "C" void kernel_launch(void* const* d_in, const int* in_sizes, int n_in, void* d_out, int out_size) {
  (void)in_sizes; (void)n_in; (void)out_size;
  void* fp = nullptr;
  cudaDriverEntryPointQueryResult qr;
  if (cudaGetDriverEntryPoint("cuTensorMapEncodeTiled", &fp, cudaEnableDefault, &qr) != cudaSuccess || !fp) return;
  EncodeFn fn = (EncodeFn)fp;
  TMaps tm;
  tm.zero = 0;
  bool ok = true;
  for (int b = 0; b < 2; b++) {
    tm.xp[b] = d_in[3 * b]; tm.wp[b] = d_in[3 * b + 1];
    {
      const cuuint64_t dims[2] = {2048, 1024}, str[1] = {4096};
      const cuuint32_t box[2] = {64, 128};
      ok &= encode(fn, &tm.x[b], d_in[3 * b + 0], 2, dims, str, box);
      ok &= encode(fn, &tm.x0[b], d_in[3 * b + 0], 2, dims, str, box, CU_TENSOR_MAP_L2_PROMOTION_L2_128B);
    }
    {
      const cuuint64_t dims[3] = {1024, 1024, 3}, str[2] = {6144, 2048};
      const cuuint32_t box[3] = {64, 32, 3};
      ok &= encode(fn, &tm.w[b], d_in[3 * b + 1], 3, dims, str, box);
      ok &= encode(fn, &tm.w0[b], d_in[3 * b + 1], 3, dims, str, box, CU_TENSOR_MAP_L2_PROMOTION_L2_128B);
    }
    {
      const cuuint64_t dims[3] = {64, 1024, 16}, str[2] = {2048, 128};
      const cuuint32_t box[3] = {64, 32, 4};
      ok &= encode(fn, &tm.wo[b], d_in[3 * b + 2], 3, dims, str, box);
    }
  }
  {
    const cuuint64_t dims[2] = {4096, 1024}, str[1] = {8192};
    const cuuint32_t box[2] = {64, 16};
    ok &= encode(fn, &tm.out, d_out, 2, dims, str, box);
  }
  if (!ok) return;
  cudaFuncSetAttribute(fused_kernel, cudaFuncAttributeMaxDynamicSharedMemorySize, SMEM_BYTES);
  fused_kernel<<<NUM_CTAS, NUM_THREADS, SMEM_BYTES>>>(tm);
}
```

```cpp
#include <cuda_runtime.h>
#include <cuda_bf16.h>
#include <cuda.h>
#include <stdint.h>
#include <type_traits>

namespace {

__device__ __forceinline__ void wgmma_n192(float (&d)[128], uint64_t da, uint64_t db, int scale_d) {
  asm volatile("{\n.reg .pred p;\nsetp.ne.b32 p, %98, 0;\n"
    "wgmma.mma_async.sync.aligned.m64n192k16.f32.bf16.bf16 "
    "{%0, %1, %2, %3, %4, %5, %6, %7, %8, %9, %10, %11, %12, %13, %14, %15, "
    "%16, %17, %18, %19, %20, %21, %22, %23, %24, %25, %26, %27, %28, %29, %30, %31, "
    "%32, %33, %34, %35, %36, %37, %38, %39, %40, %41, %42, %43, %44, %45, %46, %47, "
    "%48, %49, %50, %51, %52, %53, %54, %55, %56, %57, %58, %59, %60, %61, %62, %63, "
    "%64, %65, %66, %67, %68, %69, %70, %71, %72, %73, %74, %75, %76, %77, %78, %79, "
    "%80, %81, %82, %83, %84, %85, %86, %87, %88, %89, %90, %91, %92, %93, %94, %95}, "
    "%96, %97, p, 1, 1, 0, 1;\n}\n"
    : "+f"(d[0]), "+f"(d[1]), "+f"(d[2]), "+f"(d[3]), "+f"(d[4]), "+f"(d[5]), "+f"(d[6]), "+f"(d[7]),
      "+f"(d[8]), "+f"(d[9]), "+f"(d[10]), "+f"(d[11]), "+f"(d[12]), "+f"(d[13]), "+f"(d[14]), "+f"(d[15]),
      "+f"(d[16]), "+f"(d[17]), "+f"(d[18]), "+f"(d[19]), "+f"(d[20]), "+f"(d[21]), "+f"(d[22]), "+f"(d[23]),
      "+f"(d[24]), "+f"(d[25]), "+f"(d[26]), "+f"(d[27]), "+f"(d[28]), "+f"(d[29]), "+f"(d[30]), "+f"(d[31]),
      "+f"(d[32]), "+f"(d[33]), "+f"(d[34]), "+f"(d[35]), "+f"(d[36]), "+f"(d[37]), "+f"(d[38]), "+f"(d[39]),
      "+f"(d[40]), "+f"(d[41]), "+f"(d[42]), "+f"(d[43]), "+f"(d[44]), "+f"(d[45]), "+f"(d[46]), "+f"(d[47]),
      "+f"(d[48]), "+f"(d[49]), "+f"(d[50]), "+f"(d[51]), "+f"(d[52]), "+f"(d[53]), "+f"(d[54]), "+f"(d[55]),
      "+f"(d[56]), "+f"(d[57]), "+f"(d[58]), "+f"(d[59]), "+f"(d[60]), "+f"(d[61]), "+f"(d[62]), "+f"(d[63]),
      "+f"(d[64]), "+f"(d[65]), "+f"(d[66]), "+f"(d[67]), "+f"(d[68]), "+f"(d[69]), "+f"(d[70]), "+f"(d[71]),
      "+f"(d[72]), "+f"(d[73]), "+f"(d[74]), "+f"(d[75]), "+f"(d[76]), "+f"(d[77]), "+f"(d[78]), "+f"(d[79]),
      "+f"(d[80]), "+f"(d[81]), "+f"(d[82]), "+f"(d[83]), "+f"(d[84]), "+f"(d[85]), "+f"(d[86]), "+f"(d[87]),
      "+f"(d[88]), "+f"(d[89]), "+f"(d[90]), "+f"(d[91]), "+f"(d[92]), "+f"(d[93]), "+f"(d[94]), "+f"(d[95])
    : "l"(da), "l"(db), "r"(scale_d));
}

__device__ __forceinline__ void wgmma_n256(float (&d)[128], uint64_t da, uint64_t db, int scale_d) {
  asm volatile("{\n.reg .pred p;\nsetp.ne.b32 p, %130, 0;\n"
    "wgmma.mma_async.sync.aligned.m64n256k16.f32.bf16.bf16 "
    "{%0, %1, %2, %3, %4, %5, %6, %7, %8, %9, %10, %11, %12, %13, %14, %15, "
    "%16, %17, %18, %19, %20, %21, %22, %23, %24, %25, %26, %27, %28, %29, %30, %31, "
    "%32, %33, %34, %35, %36, %37, %38, %39, %40, %41, %42, %43, %44, %45, %46, %47, "
    "%48, %49, %50, %51, %52, %53, %54, %55, %56, %57, %58, %59, %60, %61, %62, %63, "
    "%64, %65, %66, %67, %68, %69, %70, %71, %72, %73, %74, %75, %76, %77, %78, %79, "
    "%80, %81, %82, %83, %84, %85, %86, %87, %88, %89, %90, %91, %92, %93, %94, %95, "
    "%96, %97, %98, %99, %100, %101, %102, %103, %104, %105, %106, %107, %108, %109, %110, %111, "
    "%112, %113, %114, %115, %116, %117, %118, %119, %120, %121, %122, %123, %124, %125, %126, %127}, "
    "%128, %129, p, 1, 1, 0, 1;\n}\n"
    : "+f"(d[0]), "+f"(d[1]), "+f"(d[2]), "+f"(d[3]), "+f"(d[4]), "+f"(d[5]), "+f"(d[6]), "+f"(d[7]),
      "+f"(d[8]), "+f"(d[9]), "+f"(d[10]), "+f"(d[11]), "+f"(d[12]), "+f"(d[13]), "+f"(d[14]), "+f"(d[15]),
      "+f"(d[16]), "+f"(d[17]), "+f"(d[18]), "+f"(d[19]), "+f"(d[20]), "+f"(d[21]), "+f"(d[22]), "+f"(d[23]),
      "+f"(d[24]), "+f"(d[25]), "+f"(d[26]), "+f"(d[27]), "+f"(d[28]), "+f"(d[29]), "+f"(d[30]), "+f"(d[31]),
      "+f"(d[32]), "+f"(d[33]), "+f"(d[34]), "+f"(d[35]), "+f"(d[36]), "+f"(d[37]), "+f"(d[38]), "+f"(d[39]),
      "+f"(d[40]), "+f"(d[41]), "+f"(d[42]), "+f"(d[43]), "+f"(d[44]), "+f"(d[45]), "+f"(d[46]), "+f"(d[47]),
      "+f"(d[48]), "+f"(d[49]), "+f"(d[50]), "+f"(d[51]), "+f"(d[52]), "+f"(d[53]), "+f"(d[54]), "+f"(d[55]),
      "+f"(d[56]), "+f"(d[57]), "+f"(d[58]), "+f"(d[59]), "+f"(d[60]), "+f"(d[61]), "+f"(d[62]), "+f"(d[63]),
      "+f"(d[64]), "+f"(d[65]), "+f"(d[66]), "+f"(d[67]), "+f"(d[68]), "+f"(d[69]), "+f"(d[70]), "+f"(d[71]),
      "+f"(d[72]), "+f"(d[73]), "+f"(d[74]), "+f"(d[75]), "+f"(d[76]), "+f"(d[77]), "+f"(d[78]), "+f"(d[79]),
      "+f"(d[80]), "+f"(d[81]), "+f"(d[82]), "+f"(d[83]), "+f"(d[84]), "+f"(d[85]), "+f"(d[86]), "+f"(d[87]),
      "+f"(d[88]), "+f"(d[89]), "+f"(d[90]), "+f"(d[91]), "+f"(d[92]), "+f"(d[93]), "+f"(d[94]), "+f"(d[95]),
      "+f"(d[96]), "+f"(d[97]), "+f"(d[98]), "+f"(d[99]), "+f"(d[100]), "+f"(d[101]), "+f"(d[102]), "+f"(d[103]),
      "+f"(d[104]), "+f"(d[105]), "+f"(d[106]), "+f"(d[107]), "+f"(d[108]), "+f"(d[109]), "+f"(d[110]), "+f"(d[111]),
      "+f"(d[112]), "+f"(d[113]), "+f"(d[114]), "+f"(d[115]), "+f"(d[116]), "+f"(d[117]), "+f"(d[118]), "+f"(d[119]),
      "+f"(d[120]), "+f"(d[121]), "+f"(d[122]), "+f"(d[123]), "+f"(d[124]), "+f"(d[125]), "+f"(d[126]), "+f"(d[127])
    : "l"(da), "l"(db), "r"(scale_d));
}

template <int O>
__device__ __forceinline__ void wgmma_n128(float (&d)[128], uint64_t da, uint64_t db, int scale_d) {
  asm volatile("{\n.reg .pred p;\nsetp.ne.b32 p, %66, 0;\n"
    "wgmma.mma_async.sync.aligned.m64n128k16.f32.bf16.bf16 "
    "{%0, %1, %2, %3, %4, %5, %6, %7, %8, %9, %10, %11, %12, %13, %14, %15, "
    "%16, %17, %18, %19, %20, %21, %22, %23, %24, %25, %26, %27, %28, %29, %30, %31, "
    "%32, %33, %34, %35, %36, %37, %38, %39, %40, %41, %42, %43, %44, %45, %46, %47, "
    "%48, %49, %50, %51, %52, %53, %54, %55, %56, %57, %58, %59, %60, %61, %62, %63}, "
    "%64, %65, p, 1, 1, 0, 1;\n}\n"
    : "+f"(d[O + 0]), "+f"(d[O + 1]), "+f"(d[O + 2]), "+f"(d[O + 3]), "+f"(d[O + 4]), "+f"(d[O + 5]), "+f"(d[O + 6]), "+f"(d[O + 7]),
      "+f"(d[O + 8]), "+f"(d[O + 9]), "+f"(d[O + 10]), "+f"(d[O + 11]), "+f"(d[O + 12]), "+f"(d[O + 13]), "+f"(d[O + 14]), "+f"(d[O + 15]),
      "+f"(d[O + 16]), "+f"(d[O + 17]), "+f"(d[O + 18]), "+f"(d[O + 19]), "+f"(d[O + 20]), "+f"(d[O + 21]), "+f"(d[O + 22]), "+f"(d[O + 23]),
      "+f"(d[O + 24]), "+f"(d[O + 25]), "+f"(d[O + 26]), "+f"(d[O + 27]), "+f"(d[O + 28]), "+f"(d[O + 29]), "+f"(d[O + 30]), "+f"(d[O + 31]),
      "+f"(d[O + 32]), "+f"(d[O + 33]), "+f"(d[O + 34]), "+f"(d[O + 35]), "+f"(d[O + 36]), "+f"(d[O + 37]), "+f"(d[O + 38]), "+f"(d[O + 39]),
      "+f"(d[O + 40]), "+f"(d[O + 41]), "+f"(d[O + 42]), "+f"(d[O + 43]), "+f"(d[O + 44]), "+f"(d[O + 45]), "+f"(d[O + 46]), "+f"(d[O + 47]),
      "+f"(d[O + 48]), "+f"(d[O + 49]), "+f"(d[O + 50]), "+f"(d[O + 51]), "+f"(d[O + 52]), "+f"(d[O + 53]), "+f"(d[O + 54]), "+f"(d[O + 55]),
      "+f"(d[O + 56]), "+f"(d[O + 57]), "+f"(d[O + 58]), "+f"(d[O + 59]), "+f"(d[O + 60]), "+f"(d[O + 61]), "+f"(d[O + 62]), "+f"(d[O + 63])
    : "l"(da), "l"(db), "r"(scale_d));
}

template <int O>
__device__ __forceinline__ void wgmma_n128_rs(float (&d)[128], const uint32_t (&a)[4], uint64_t db) {
  asm volatile("wgmma.mma_async.sync.aligned.m64n128k16.f32.bf16.bf16 "
    "{%0, %1, %2, %3, %4, %5, %6, %7, %8, %9, %10, %11, %12, %13, %14, %15, "
    "%16, %17, %18, %19, %20, %21, %22, %23, %24, %25, %26, %27, %28, %29, %30, %31, "
    "%32, %33, %34, %35, %36, %37, %38, %39, %40, %41, %42, %43, %44, %45, %46, %47, "
    "%48, %49, %50, %51, %52, %53, %54, %55, %56, %57, %58, %59, %60, %61, %62, %63}, "
    "{%64, %65, %66, %67}, %68, 1, 1, 1, 1;\n"
    : "+f"(d[O + 0]), "+f"(d[O + 1]), "+f"(d[O + 2]), "+f"(d[O + 3]), "+f"(d[O + 4]), "+f"(d[O + 5]), "+f"(d[O + 6]), "+f"(d[O + 7]),
      "+f"(d[O + 8]), "+f"(d[O + 9]), "+f"(d[O + 10]), "+f"(d[O + 11]), "+f"(d[O + 12]), "+f"(d[O + 13]), "+f"(d[O + 14]), "+f"(d[O + 15]),
      "+f"(d[O + 16]), "+f"(d[O + 17]), "+f"(d[O + 18]), "+f"(d[O + 19]), "+f"(d[O + 20]), "+f"(d[O + 21]), "+f"(d[O + 22]), "+f"(d[O + 23]),
      "+f"(d[O + 24]), "+f"(d[O + 25]), "+f"(d[O + 26]), "+f"(d[O + 27]), "+f"(d[O + 28]), "+f"(d[O + 29]), "+f"(d[O + 30]), "+f"(d[O + 31]),
      "+f"(d[O + 32]), "+f"(d[O + 33]), "+f"(d[O + 34]), "+f"(d[O + 35]), "+f"(d[O + 36]), "+f"(d[O + 37]), "+f"(d[O + 38]), "+f"(d[O + 39]),
      "+f"(d[O + 40]), "+f"(d[O + 41]), "+f"(d[O + 42]), "+f"(d[O + 43]), "+f"(d[O + 44]), "+f"(d[O + 45]), "+f"(d[O + 46]), "+f"(d[O + 47]),
      "+f"(d[O + 48]), "+f"(d[O + 49]), "+f"(d[O + 50]), "+f"(d[O + 51]), "+f"(d[O + 52]), "+f"(d[O + 53]), "+f"(d[O + 54]), "+f"(d[O + 55]),
      "+f"(d[O + 56]), "+f"(d[O + 57]), "+f"(d[O + 58]), "+f"(d[O + 59]), "+f"(d[O + 60]), "+f"(d[O + 61]), "+f"(d[O + 62]), "+f"(d[O + 63])
    : "r"(a[0]), "r"(a[1]), "r"(a[2]), "r"(a[3]), "l"(db));
}

constexpr int NUM_CTAS = 128;
constexpr int NUM_THREADS = 384;
constexpr int G1_STAGES = 5, G2_STAGES = 4;
constexpr uint32_t A_BYTES = 16384;
constexpr uint32_t G1_STAGE = 40960;
constexpr uint32_t G2_STAGE = 49152;
constexpr uint32_t RING_BYTES = G1_STAGES * G1_STAGE;
constexpr uint32_t OFF_X = RING_BYTES;
constexpr uint32_t OFF_BAR = OFF_X + 9 * 2048;
constexpr uint32_t SMEM_BYTES = OFF_BAR + 512;
constexpr uint32_t SPIN_LIMIT = 1u << 21;

struct alignas(64) TMaps {
  CUtensorMap x[2], w[2], wo[2], out;
  CUtensorMap x0[2], w0[2];
  const void* xp[2];
  const void* wp[2];
  uint32_t zero;
};

__device__ __align__(1024) uint4 g_o[32 * 16 * 1024];
__device__ __align__(1024) ulonglong2 g_halo[NUM_CTAS * 4 * 256];
__device__ unsigned g_o_ready[32 * 4];
__device__ unsigned g_epoch[NUM_CTAS];

__device__ __forceinline__ void mbar_init(uint32_t bar, uint32_t count) {
  asm volatile("mbarrier.init.shared::cta.b64 [%0], %1;" ::"r"(bar), "r"(count) : "memory");
}
__device__ __forceinline__ bool mbar_try_wait(uint32_t bar, uint32_t parity) {
  uint32_t ok;
  asm volatile("{\n.reg .pred p;\nmbarrier.try_wait.parity.shared::cta.b64 p, [%1], %2;\nselp.u32 %0, 1, 0, p;\n}\n"
               : "=r"(ok) : "r"(bar), "r"(parity) : "memory");
  return ok != 0;
}
__device__ __forceinline__ void mbar_wait(uint32_t bar, uint32_t parity) {
  uint32_t spins = 0;
  while (!mbar_try_wait(bar, parity)) { if (++spins > SPIN_LIMIT) __trap(); }
}
__device__ __forceinline__ void mbar_arrive(uint32_t bar) {
  asm volatile("mbarrier.arrive.shared::cta.b64 _, [%0];" ::"r"(bar) : "memory");
}
__device__ __forceinline__ void mbar_arrive_cluster(uint32_t bar_cluster_addr) {
  asm volatile("mbarrier.arrive.shared::cluster.b64 _, [%0];" ::"r"(bar_cluster_addr) : "memory");
}
__device__ __forceinline__ void mbar_expect_tx(uint32_t bar, uint32_t bytes) {
  asm volatile("mbarrier.arrive.expect_tx.shared::cta.b64 _, [%0], %1;" ::"r"(bar), "r"(bytes) : "memory");
}
__device__ __forceinline__ uint32_t mapa(uint32_t addr, uint32_t rank) {
  uint32_t r; asm("mapa.shared::cluster.u32 %0, %1, %2;" : "=r"(r) : "r"(addr), "r"(rank)); return r;
}
__device__ __forceinline__ void tma_load_2d(uint32_t dst, const CUtensorMap* m, int c0, int c1, uint32_t bar) {
  asm volatile("cp.async.bulk.tensor.2d.shared::cluster.global.mbarrier::complete_tx::bytes [%0], [%1, {%3, %4}], [%2];"
               ::"r"(dst), "l"(m), "r"(bar), "r"(c0), "r"(c1) : "memory");
}
__device__ __forceinline__ void tma_load_3d(uint32_t dst, const CUtensorMap* m, int c0, int c1, int c2, uint32_t bar) {
  asm volatile("cp.async.bulk.tensor.3d.shared::cluster.global.mbarrier::complete_tx::bytes [%0], [%1, {%3, %4, %5}], [%2];"
               ::"r"(dst), "l"(m), "r"(bar), "r"(c0), "r"(c1), "r"(c2) : "memory");
}
__device__ __forceinline__ void tma_load_3d_mc(uint32_t dst, const CUtensorMap* m, int c0, int c1, int c2, uint32_t bar, uint16_t mask) {
  asm volatile("cp.async.bulk.tensor.3d.shared::cluster.global.mbarrier::complete_tx::bytes.multicast::cluster [%0], [%1, {%3, %4, %5}], [%2], %6;"
               ::"r"(dst), "l"(m), "r"(bar), "r"(c0), "r"(c1), "r"(c2), "h"(mask) : "memory");
}
__device__ __forceinline__ void tma_store_2d(const CUtensorMap* m, int c0, int c1, uint32_t src) {
  asm volatile("cp.async.bulk.tensor.2d.global.shared::cta.bulk_group [%0, {%2, %3}], [%1];"
               ::"l"(m), "r"(src), "r"(c0), "r"(c1) : "memory");
}
__device__ __forceinline__ void bulk_load(uint32_t dst, const void* src, uint32_t bytes, uint32_t bar) {
  asm volatile("cp.async.bulk.shared::cluster.global.mbarrier::complete_tx::bytes [%0], [%1], %2, [%3];"
               ::"r"(dst), "l"(src), "r"(bytes), "r"(bar) : "memory");
}
__device__ __forceinline__ void bulk_store(void* dst, uint32_t src, uint32_t bytes) {
  asm volatile("cp.async.bulk.global.shared::cta.bulk_group [%0], [%1], %2;" ::"l"(dst), "r"(src), "r"(bytes) : "memory");
}
__device__ __forceinline__ void bulk_commit() { asm volatile("cp.async.bulk.commit_group;" ::: "memory"); }
__device__ __forceinline__ void bulk_wait0() { asm volatile("cp.async.bulk.wait_group 0;" ::: "memory"); }
__device__ __forceinline__ void bulk_wait0_read() { asm volatile("cp.async.bulk.wait_group.read 0;" ::: "memory"); }
__device__ __forceinline__ void fence_async_smem() { asm volatile("fence.proxy.async.shared::cta;" ::: "memory"); }
__device__ __forceinline__ void prefetch_tmap(const CUtensorMap* m) {
  asm volatile("prefetch.tensormap [%0];" ::"l"(m) : "memory");
}
__device__ __forceinline__ void wgmma_fence() { asm volatile("wgmma.fence.sync.aligned;" ::: "memory"); }
__device__ __forceinline__ void wgmma_commit() { asm volatile("wgmma.commit_group.sync.aligned;" ::: "memory"); }
template <int N> __device__ __forceinline__ void wgmma_wait() { asm volatile("wgmma.wait_group.sync.aligned %0;" ::"n"(N) : "memory"); }
template <int B, int N> __device__ __forceinline__ void fence_acc(float (&d)[128]) {
#pragma unroll
  for (int i = B; i < N; i++) asm volatile("" : "+f"(d[i])::"memory");
}
__device__ __forceinline__ void bar_sync(int id) { asm volatile("bar.sync %0, 256;" ::"r"(id) : "memory"); }
__device__ __forceinline__ void bar_arrive(int id) { asm volatile("bar.arrive %0, 256;" ::"r"(id) : "memory"); }
__device__ __forceinline__ void sched_fence(uint32_t zero) {
  asm volatile("{\n.reg .pred p;\nsetp.ne.u32 p, %0, 0;\n@p trap;\n}\n" ::"r"(zero) : "memory");
}
__device__ __forceinline__ uint64_t desc_kmajor(uint32_t addr) {
  return (uint64_t)((addr & 0x3FFFF) >> 4) | (1ull << 16) | (64ull << 32) | (1ull << 62);
}
__device__ __forceinline__ uint64_t desc_mnmajor(uint32_t addr) {
  return (uint64_t)((addr & 0x3FFFF) >> 4) | (256ull << 16) | (64ull << 32) | (1ull << 62);
}
__device__ __forceinline__ uint32_t pack_bf16(float lo, float hi) {
  uint32_t r; asm("cvt.rn.bf16x2.f32 %0, %1, %2;" : "=r"(r) : "f"(hi), "f"(lo)); return r;
}
__device__ __forceinline__ void stsm_x4(uint32_t addr, uint32_t r0, uint32_t r1, uint32_t r2, uint32_t r3) {
  asm volatile("stmatrix.sync.aligned.m8n8.x4.shared.b16 [%0], {%1, %2, %3, %4};" ::"r"(addr), "r"(r0), "r"(r1), "r"(r2), "r"(r3) : "memory");
}
__device__ __forceinline__ void stsm_x4_t(uint32_t addr, uint32_t r0, uint32_t r1, uint32_t r2, uint32_t r3) {
  asm volatile("stmatrix.sync.aligned.m8n8.x4.trans.shared.b16 [%0], {%1, %2, %3, %4};" ::"r"(addr), "r"(r0), "r"(r1), "r"(r2), "r"(r3) : "memory");
}
__device__ __forceinline__ void ldsm_x4(uint32_t addr, uint32_t (&r)[4]) {
  asm volatile("ldmatrix.sync.aligned.m8n8.x4.shared.b16 {%0, %1, %2, %3}, [%4];" : "=r"(r[0]), "=r"(r[1]), "=r"(r[2]), "=r"(r[3]) : "r"(addr) : "memory");
}
__device__ __forceinline__ uint32_t movm_t(uint32_t a) {
  uint32_t d; asm volatile("movmatrix.sync.aligned.m8n8.trans.b16 %0, %1;" : "=r"(d) : "r"(a)); return d;
}
__device__ __forceinline__ void mma_init(float (&c)[4], uint32_t a0, uint32_t a1, uint32_t a2, uint32_t a3, uint32_t b0, uint32_t b1) {
  asm volatile("mma.sync.aligned.m16n8k16.row.col.f32.bf16.bf16.f32 {%0, %1, %2, %3}, {%4, %5, %6, %7}, {%8, %9}, {%10, %10, %10, %10};"
               : "=f"(c[0]), "=f"(c[1]), "=f"(c[2]), "=f"(c[3]) : "r"(a0), "r"(a1), "r"(a2), "r"(a3), "r"(b0), "r"(b1), "f"(0.f));
}
__device__ __forceinline__ void mma_acc(float (&c)[4], uint32_t a0, uint32_t a1, uint32_t a2, uint32_t a3, uint32_t b0, uint32_t b1) {
  asm volatile("mma.sync.aligned.m16n8k16.row.col.f32.bf16.bf16.f32 {%0, %1, %2, %3}, {%4, %5, %6, %7}, {%8, %9}, {%0, %1, %2, %3};"
               : "+f"(c[0]), "+f"(c[1]), "+f"(c[2]), "+f"(c[3]) : "r"(a0), "r"(a1), "r"(a2), "r"(a3), "r"(b0), "r"(b1));
}
__device__ __forceinline__ float ex2(float x) { float y; asm("ex2.approx.ftz.f32 %0, %1;" : "=f"(y) : "f"(x)); return y; }
__device__ __forceinline__ unsigned ld_acquire(const unsigned* p) {
  unsigned v; asm volatile("ld.acquire.gpu.global.u32 %0, [%1];" : "=r"(v) : "l"(p) : "memory"); return v;
}
__device__ __forceinline__ void wait_flag(const unsigned* p, unsigned target) {
  uint32_t spins = 0;
  while ((int)(ld_acquire(p) - target) < 0) { if (++spins > SPIN_LIMIT) __trap(); __nanosleep(20); }
}
__device__ __forceinline__ uint4 lds128(uint32_t addr) {
  uint4 v; asm volatile("ld.shared.v4.u32 {%0, %1, %2, %3}, [%4];" : "=r"(v.x), "=r"(v.y), "=r"(v.z), "=r"(v.w) : "r"(addr) : "memory"); return v;
}
__device__ __forceinline__ void sts128(uint32_t addr, uint32_t a, uint32_t b, uint32_t c, uint32_t d) {
  asm volatile("st.shared.v4.u32 [%0], {%1, %2, %3, %4};" ::"r"(addr), "r"(a), "r"(b), "r"(c), "r"(d) : "memory");
}

template <int N>
__device__ __forceinline__ void softmax_exp(const uint32_t (&qk)[N], float (&ex)[N][2]) {
  constexpr float kScale = 0.17677669529663687f, kLog2e = 1.4426950408889634f;
  float m[N];
#pragma unroll
  for (int i = 0; i < N; i++) {
    const uint32_t p = pack_bf16(__uint_as_float(qk[i] << 16) * kScale, __uint_as_float(qk[i] & 0xffff0000u) * kScale);
    ex[i][0] = __uint_as_float(p << 16);
    ex[i][1] = __uint_as_float(p & 0xffff0000u);
    m[i] = fmaxf(ex[i][0], ex[i][1]);
  }
#pragma unroll
  for (int i = 0; i < N; i++) m[i] = fmaxf(m[i], __shfl_xor_sync(0xffffffffu, m[i], 1));
#pragma unroll
  for (int i = 0; i < N; i++) m[i] = fmaxf(m[i], __shfl_xor_sync(0xffffffffu, m[i], 2));
#pragma unroll
  for (int i = 0; i < N; i++) { ex[i][0] = ex2((ex[i][0] - m[i]) * kLog2e); ex[i][1] = ex2((ex[i][1] - m[i]) * kLog2e); }
}
template <int N>
__device__ __forceinline__ void softmax_norm(const float (&ex)[N][2], uint32_t lo_mask, uint32_t (&b_lo)[N], uint32_t (&b_hi)[N]) {
  float s[N];
#pragma unroll
  for (int i = 0; i < N; i++) s[i] = ex[i][0] + ex[i][1];
#pragma unroll
  for (int i = 0; i < N; i++) s[i] += __shfl_xor_sync(0xffffffffu, s[i], 1);
#pragma unroll
  for (int i = 0; i < N; i++) s[i] += __shfl_xor_sync(0xffffffffu, s[i], 2);
#pragma unroll
  for (int i = 0; i < N; i++) {
    float r;
    asm("rcp.approx.ftz.f32 %0, %1;" : "=f"(r) : "f"(s[i]));
    const uint32_t p = pack_bf16(ex[i][0] * r, ex[i][1] * r);
    b_lo[i] = p & lo_mask;
    b_hi[i] = p & ~lo_mask;
  }
}

__global__ void __cluster_dims__(2, 1, 1) __launch_bounds__(NUM_THREADS, 1)
fused_kernel(const __grid_constant__ TMaps tm) {
  extern __shared__ __align__(1024) uint8_t smem_raw[];
  const uint32_t sb = (uint32_t)__cvta_generic_to_shared(smem_raw);
  const int warp = __shfl_sync(0xffffffffu, threadIdx.x >> 5, 0), lane = threadIdx.x & 31;
  const int e = blockIdx.x & 1;
  int cg, rb, br;
  {
    const int c = blockIdx.x >> 1;
    int q, i;
    if (c < 4) { q = 0; i = c; }
    else if (c < 36) { q = 1 + ((c - 4) & 7); i = (c - 4) >> 3; }
    else { q = 9 + (c - 36) % 7; i = (c - 36) / 7; }
    cg = i; rb = q & 7; br = q >> 3;
  }
  const int cta = e + 2 * cg + 8 * rb + 64 * br;
  const uint32_t bar_full1 = sb + OFF_BAR, bar_empty1 = bar_full1 + 64, bar_full2 = bar_full1 + 128,
                 bar_empty2 = bar_full1 + 160, bar_o_full = bar_full1 + 192, bar_o_empty = bar_full1 + 200,
                 bar_o = bar_full1 + 208  , bar_x = bar_full1 + 240  ;

  if (warp == 8 && lane == 0) {
    prefetch_tmap(&tm.x0[br]); prefetch_tmap(&tm.w0[br]);
    prefetch_tmap(&tm.x[br]); prefetch_tmap(&tm.w[br]);
    for (int s = 0; s < G1_STAGES; s++) mbar_init(bar_full1 + 8 * s, 1);
    asm volatile("fence.mbarrier_init.release.cluster;" ::: "memory");
  } else if (warp == 9 && lane == 0) {
    for (int s = 0; s < G1_STAGES; s++) mbar_init(bar_empty1 + 8 * s, 16);
    for (int s = 0; s < G2_STAGES; s++) { mbar_init(bar_full2 + 8 * s, 1); mbar_init(bar_empty2 + 8 * s, 16); }
    for (int s = 0; s < 18; s++) mbar_init(bar_x + 8 * s, 1);
    mbar_init(bar_o_full, 8); mbar_init(bar_o_empty, 3);
    for (int t = 0; t < 4; t++) mbar_init(bar_o + 8 * t, 1);
    asm volatile("fence.mbarrier_init.release.cluster;" ::: "memory");
  } else if (warp < 2) {
    if (warp == 0) {
      const char* p = (const char*)tm.xp[br] + (size_t)(rb * 128 + cg * 32 + lane) * 4096 + e * 2048;
      asm volatile("prefetch.global.L2 [%0];" ::"l"(p));
    } else if (lane < 12) {
      const int l = rb * 2 + e + 16 * lane;
      const char* p = (const char*)tm.wp[br] + (size_t)(l / 3) * 6144 + (l % 3) * 2048 + cg * 512;
      asm volatile("prefetch.global.L2 [%0];" ::"l"(p));
    }
  }
  __syncwarp();
  asm volatile("barrier.cluster.arrive.relaxed.aligned;" ::: "memory");

  if (warp < 8) {
    asm volatile("setmaxnreg.inc.sync.aligned.u32 232;");
    asm volatile("barrier.cluster.wait.aligned;" ::: "memory");
    const int wg = warp >> 2;
    float acc[128], acc2[128];
    uint32_t pk[48];
    uint32_t kq[16], vq[16];
    float sf[8][4], of[8][4];
    float pe[4][2];
    uint32_t b_lo[4], b_hi[4];
    const bool rel_any = lane < 2;
    const uint32_t rel_base = mapa(bar_full1, lane == 0 ? e : (e ^ 1));
    const int g = lane >> 2, tq = lane & 3;
    const uint32_t lo_mask = (2 * tq > g ? 0xffffu : 0u) | (2 * tq + 1 > g ? 0xffff0000u : 0u);
    const bool seq_start = (rb == 0 && warp == 0);
    const uint32_t slot = sb + OFF_X + warp * 2048;
    int s = 1, ph = 0;

    enum { XK = 1, MH = 2, XV = 4, ML = 8, RK = 16, S1 = 32, S2 = 64, RV = 128, ST0 = 256, ST1 = 512, QK = 1024, PV = 2048 };
    auto attn = [&](auto phase, int ta) __attribute__((always_inline)) {
      constexpr int P = decltype(phase)::value;
      if constexpr ((P & XK) != 0) {
        if (ta > 0) mbar_wait(bar_o_empty, (ta - 1) & 1);
        sts128(slot + 2048 + lane * 16, pk[17] ^ tm.zero, pk[19] ^ tm.zero, pk[21] ^ tm.zero, pk[23] ^ tm.zero);
        sts128(slot + 2560 + lane * 16, pk[25] ^ tm.zero, pk[27] ^ tm.zero, pk[29] ^ tm.zero, pk[31] ^ tm.zero);
        __syncwarp();
        if (lane == 0) mbar_arrive(bar_x + 16 * warp + 16);
      }
      if constexpr ((P & MH) != 0) {
#pragma unroll
        for (int i = 1; i < 16; i += 2) pk[32 + i] = movm_t(pk[32 + i]);
      }
      if constexpr ((P & XV) != 0) {
        sts128(slot + 3072 + lane * 16, pk[33] ^ tm.zero, pk[35] ^ tm.zero, pk[37] ^ tm.zero, pk[39] ^ tm.zero);
        sts128(slot + 3584 + lane * 16, pk[41] ^ tm.zero, pk[43] ^ tm.zero, pk[45] ^ tm.zero, pk[47] ^ tm.zero);
        __syncwarp();
        if (lane == 0) mbar_arrive(bar_x + 16 * warp + 24);
      }
      if constexpr ((P & ML) != 0) {
#pragma unroll
        for (int i = 0; i < 16; i += 2) pk[32 + i] = movm_t(pk[32 + i]);
      }
      if constexpr ((P & S1) != 0) {
        if (seq_start) sf[0][0] = sf[0][1] = sf[2][0] = sf[2][1] = -INFINITY;
        uint32_t qk[4];
#pragma unroll
        for (int i = 0; i < 4; i++) qk[i] = movm_t(pack_bf16(g > 2 * tq ? sf[i][0] : sf[i][2], g > 2 * tq + 1 ? sf[i][1] : sf[i][3]));
        softmax_exp<4>(qk, pe);
      }
      if constexpr ((P & S2) != 0) softmax_norm<4>(pe, lo_mask, b_lo, b_hi);
      if constexpr ((P & (RK | RV)) != 0) {
        constexpr int V = (P & RV) != 0;
#pragma unroll
        for (int i = 0; i < (V ? 32 : 16); i++) (V ? of : sf)[i / 4][i % 4] = 0.f;
        mbar_wait(bar_x + 16 * warp + 8 * V, ta & 1);
        const uint4 x0 = lds128(slot + V * 1024 + lane * 16), x1 = lds128(slot + V * 1024 + 512 + lane * 16);
        const uint32_t xx[8] = {x0.x, x0.y, x0.z, x0.w, x1.x, x1.y, x1.z, x1.w};
#pragma unroll
        for (int i = 0; i < 8; i++) {
          if constexpr (V) { vq[(i / 2) * 4 + (i & 1)] = xx[i] ^ tm.zero; vq[(i / 2) * 4 + 2 + (i & 1)] = pk[32 + 2 * i] ^ tm.zero; }
          else { kq[2 * i] = xx[i] ^ tm.zero; kq[2 * i + 1] = pk[16 + 2 * i] ^ tm.zero; }
        }
      }
      if constexpr ((P & (ST0 | ST1)) != 0) {
#pragma unroll
        for (int i = (P & ST0) ? 0 : 2; i < ((P & ST1) ? 4 : 2); i++)
          stsm_x4_t(slot + ((i & 1) * 8 + (lane & 7)) * 128 + ((((i >> 1) * 4 + (lane >> 3)) ^ (lane & 7)) << 4),
                    pack_bf16(of[2 * i][0], of[2 * i][1]), pack_bf16(of[2 * i][2], of[2 * i][3]),
                    pack_bf16(of[2 * i + 1][0], of[2 * i + 1][1]), pack_bf16(of[2 * i + 1][2], of[2 * i + 1][3]));
        if constexpr ((P & ST1) != 0) {
          fence_async_smem();
          __syncwarp();
          if (lane == 0) mbar_arrive(bar_o_full);
        }
      }
    };
    auto burst = [&](auto phase, auto from, auto to) __attribute__((always_inline)) {
      constexpr int P = decltype(phase)::value, B = decltype(from)::value, E = decltype(to)::value;
#pragma unroll
      for (int n = B; n < E; n++) {
        if constexpr (P == QK) {
          const int k = n / 4, h = (n / 2) & 1, hf = n & 1, q = 8 * h + 4 * k;
          const uint32_t* a = hf ? &pk[16 + q] : &kq[q];
          if (k == 0) mma_init(sf[2 * h + hf], a[0], a[1], a[2], a[3], pk[q + hf], pk[q + 2 + hf]);
          else mma_acc(sf[2 * h + hf], a[0], a[1], a[2], a[3], pk[q + hf], pk[q + 2 + hf]);
        } else {
          const int h = n / 4, hf = (n / 2) & 1, v = 8 * h + 4 * (n & 1);
          if (hf == 0) mma_init(of[n], vq[v], vq[v + 1], vq[v + 2], vq[v + 3], b_lo[2 * h], b_hi[2 * h]);
          else mma_init(of[n], pk[32 + v], pk[34 + v], pk[33 + v], pk[35 + v], b_lo[2 * h + 1], b_hi[2 * h + 1]);
        }
      }
    };
#define PH(n) std::integral_constant<int, n>{}
    uint32_t rel = 0;
    uint64_t da_next = desc_kmajor(sb + G1_STAGE + wg * 8192), db_next = desc_mnmajor(sb + G1_STAGE + A_BYTES);
    auto kstep = [&](auto g2, auto pre0, auto post, auto burst1, bool first, int ta, bool next_g2) __attribute__((always_inline)) {
      constexpr bool G2 = decltype(g2)::value;
      constexpr uint64_t HALF = G2 ? 1024 : 768;
      const uint64_t da = da_next, db = db_next;
      if constexpr (decltype(pre0)::value != 0) { if (wg == 0) burst(pre0, PH(0), PH(8)); }
      bar_sync(1 + wg);
      wgmma_fence();
      if constexpr (G2) {
        wgmma_n256(acc2, da, db, !first);
        wgmma_n256(acc2, da + 2, db + 128, 1);
        wgmma_n256(acc2, da + 4, db + HALF, 1);
        wgmma_n256(acc2, da + 6, db + HALF + 128, 1);
      } else {
        wgmma_n192(acc, da, db, !first);
        wgmma_n192(acc, da + 2, db + 128, 1);
        wgmma_n192(acc, da + 4, db + HALF, 1);
        wgmma_n192(acc, da + 6, db + HALF + 128, 1);
      }
      wgmma_commit();
      const bool late = decltype(burst1)::value != 0 && wg == 1;
      if (!late) bar_arrive(2 - wg);
      if (rel) mbar_arrive_cluster(rel);
      rel = rel_any ? rel_base + (G2 ? 160 : 64) + 8 * s : 0;
      if constexpr (decltype(post)::value != 0) {
        sched_fence(tm.zero);
        attn(post, ta);
      }
      if (++s == (G2 ? G2_STAGES : G1_STAGES)) s = 0;
      if (s == (G2 ? 0 : 1)) ph ^= 1;
      if (!G2 && next_g2) { s = 0; ph = 0; }
      {
        const uint32_t st = sb + s * (next_g2 ? G2_STAGE : G1_STAGE);
        uint32_t a_lo = (uint32_t)desc_kmajor(st + wg * 8192), b_lo = (uint32_t)desc_mnmajor(st + A_BYTES);
        asm volatile("" : "+r"(a_lo), "+r"(b_lo));
        da_next = (desc_kmajor(0) & ~0xffffffffull) | a_lo;
        db_next = (desc_mnmajor(0) & ~0xffffffffull) | b_lo;
      }
      mbar_wait((next_g2 ? bar_full2 : bar_full1) + 8 * s, ph);
      if constexpr (decltype(burst1)::value != 0) {
        if (late) {
          constexpr int N = 8, M = decltype(burst1)::value == QK ? 5 : 4;
          burst(burst1, PH(0), PH(N - M));
          sched_fence(tm.zero);
          bar_arrive(1);
          burst(burst1, PH(N - M), PH(N));
        }
      }
      wgmma_wait<0>();
    };
    using F = std::false_type; using T = std::true_type;
    if (wg == 1) bar_arrive(1);
    mbar_wait(bar_full1 + 8 * s, ph);

    constexpr int sc1[11] = {0, XK, MH, XV, ML, RK | QK, S1, S2, RV | PV, ST0, ST1};
    constexpr int sc2[7] = {0, XK | MH, XV, ML, RK | QK, S1 | S2 | RV | PV, ST0 | ST1};
#define KSTEP(g2, sc, i, ta, next) \
    kstep(g2, PH(sc[i] & (QK | PV)), PH(sc[i + 1] & ~(QK | PV)), PH(sc[i + 1] & (QK | PV)), i == 0, ta, next)
    kstep(F{}, PH(0), PH(0), PH(0), true, 0, false);
#pragma unroll 1
    for (int ks = 1; ks < 10; ks++) kstep(F{}, PH(0), PH(0), PH(0), false, 0, false);
#pragma unroll 1
    for (int t = 0;; t++) {
#pragma unroll 1
      for (int ks = 10; ks < 16; ks++) kstep(F{}, PH(0), PH(0), PH(0), false, 0, t == 3 && ks == 15);
      fence_acc<0, 96>(acc);
#pragma unroll
      for (int i = 0; i < 48; i++) pk[i] = pack_bf16(acc[2 * i], acc[2 * i + 1]);
      if (t == 3) break;
      KSTEP(F{}, sc1, 0, t, 0);  KSTEP(F{}, sc1, 1, t, 0); KSTEP(F{}, sc1, 2, t, 0);
      KSTEP(F{}, sc1, 3, t, 0); KSTEP(F{}, sc1, 4, t, 0); KSTEP(F{}, sc1, 5, t, 0);
      KSTEP(F{}, sc1, 6, t, 0); KSTEP(F{}, sc1, 7, t, 0); KSTEP(F{}, sc1, 8, t, 0);
      KSTEP(F{}, sc1, 9, t, 0);
    }
    KSTEP(T{}, sc2, 0, 3, 1);  KSTEP(T{}, sc2, 1, 3, 1); KSTEP(T{}, sc2, 2, 3, 1);
    KSTEP(T{}, sc2, 3, 3, 1); KSTEP(T{}, sc2, 4, 3, 1); KSTEP(T{}, sc2, 5, 3, 1);
#pragma unroll 1
    for (int ks = 6; ks < 12; ks++) kstep(T{}, PH(0), PH(0), PH(0), false, 0, true);
    if (rel) mbar_arrive_cluster(rel);
    auto store_chunk = [&](auto chunk, float (&ac)[128]) __attribute__((always_inline)) {
      constexpr int c = decltype(chunk)::value;
      const uint32_t stg = sb + c * G2_STAGE + warp * 2048;
      const int r = ((lane >> 3) & 1) * 8 + (lane & 7);
#pragma unroll
      for (int jj = 0; jj < 8; jj += 2) {
        const int j = c * 8 + jj;
        stsm_x4(stg + r * 128 + (((jj + (lane >> 4)) ^ (r & 7)) << 4), pack_bf16(ac[4 * j], ac[4 * j + 1]),
                pack_bf16(ac[4 * j + 2], ac[4 * j + 3]), pack_bf16(ac[4 * j + 4], ac[4 * j + 5]),
                pack_bf16(ac[4 * j + 6], ac[4 * j + 7]));
      }
      fence_async_smem();
      __syncwarp();
      if (lane == 0) {
        tma_store_2d(&tm.out, e * 2048 + br * 1024 + cg * 256 + c * 64, rb * 128 + warp * 16, stg);
        bulk_commit();
      }
    };
    if (wg == 0) {
      float acc3[128];
#pragma unroll
      for (int i = 0; i < 128; i++) asm volatile("mov.b32 %0, %1;" : "=f"(acc3[i]) : "f"(acc2[i]));
      auto half_step = [&](auto side, int j) __attribute__((always_inline)) {
        constexpr int R = decltype(side)::value;
        const uint64_t da = desc_kmajor(sb + j * G2_STAGE);
        const uint64_t db = desc_mnmajor(sb + j * G2_STAGE + A_BYTES) + R * 512;
        wgmma_n128<R * 64>(acc3, da, db, 1);
        wgmma_n128<R * 64>(acc3, da + 2, db + 128, 1);
        wgmma_n128<R * 64>(acc3, da + 4, db + 1024, 1);
        wgmma_n128<R * 64>(acc3, da + 6, db + 1024 + 128, 1);
      };
      bar_sync(1);
#pragma unroll 1
      for (int j = 0; j < 2; j++) { mbar_wait(bar_full2 + 8 * j, 1); wgmma_fence(); half_step(PH(0), j); half_step(PH(1), j); wgmma_commit(); }
#pragma unroll 1
      for (int j = 2; j < 4; j++) { mbar_wait(bar_full2 + 8 * j, 1); wgmma_fence(); half_step(PH(0), j); wgmma_commit(); }
      wgmma_fence();
      half_step(PH(1), 2); half_step(PH(1), 3);
      wgmma_commit();
      bar_arrive(2);
      wgmma_wait<1>();
      fence_acc<0, 64>(acc3);
      store_chunk(PH(0), acc3); store_chunk(PH(1), acc3);
      wgmma_wait<0>();
      fence_acc<64, 128>(acc3);
      store_chunk(PH(2), acc3); store_chunk(PH(3), acc3);
    } else {
      float acc3[128];
#pragma unroll
      for (int i = 0; i < 128; i++) asm volatile("mov.b32 %0, %1;" : "=f"(acc3[i]) : "f"(acc2[i]));
      uint32_t af[16][4];
      const int r = ((lane >> 3) & 1) * 8 + (lane & 7);
#pragma unroll
      for (int j = 0; j < 4; j++) {
        mbar_wait(bar_full2 + 8 * j, 1);
#pragma unroll
        for (int k = 0; k < 4; k++) ldsm_x4(sb + j * G2_STAGE + warp * 2048 + r * 128 + (((2 * k + (lane >> 4)) ^ (r & 7)) << 4), af[4 * j + k]);
      }
      bar_sync(2);
      wgmma_fence();
      const uint64_t db = desc_mnmajor(sb + A_BYTES);
#define B_OFF(i) (((i) >> 2) * (G2_STAGE >> 4) + (((i) >> 1) & 1) * 1024 + ((i) & 1) * 128)
#pragma unroll
      for (int i = 0; i < 16; i++) wgmma_n128_rs<0>(acc3, af[i], db + B_OFF(i));
      wgmma_commit();
#pragma unroll
      for (int i = 0; i < 7; i++) wgmma_n128_rs<64>(acc3, af[i], db + B_OFF(i) + 512);
      wgmma_commit();
      wgmma_wait<1>();
      fence_acc<0, 64>(acc3);
      store_chunk(PH(0), acc3);
      wgmma_fence();
#pragma unroll
      for (int i = 7; i < 12; i++) wgmma_n128_rs<64>(acc3, af[i], db + B_OFF(i) + 512);
      wgmma_commit();
      store_chunk(PH(1), acc3);
      wgmma_fence();
#pragma unroll
      for (int i = 12; i < 16; i++) wgmma_n128_rs<64>(acc3, af[i], db + B_OFF(i) + 512);
      wgmma_commit();
      wgmma_wait<0>();
      fence_acc<64, 128>(acc3);
      store_chunk(PH(2), acc3); store_chunk(PH(3), acc3);
    }
    if (lane == 0) bulk_wait0_read();
    if (threadIdx.x == 0) { atomicAdd(&g_epoch[cta], 1u); }
  } else {
    asm volatile("setmaxnreg.dec.sync.aligned.u32 40;");
    if (warp == 8 && lane == 0) {
      fence_async_smem();
      for (int it = 0; it < G1_STAGES; it++) {
        const int s = (it + 1) % G1_STAGES;
        const uint32_t st = sb + s * G1_STAGE, fb = bar_full1 + 8 * s;
        if (it > 0) { const long long c0 = clock64(); while (clock64() - c0 < 400) {} }
        mbar_expect_tx(fb, G1_STAGE);
        tma_load_2d(st, it < 4 ? &tm.x0[br] : &tm.x[br], e * 1024 + it * 64, rb * 128, fb);
        tma_load_3d(st + A_BYTES, &tm.w0[br], cg * 256, it * 64, 0, fb);
        tma_load_3d(st + A_BYTES + 12288, &tm.w0[br], cg * 256, it * 64 + 32, 0, fb);
      }
    }
    __syncwarp();
    asm volatile("barrier.cluster.wait.aligned;" ::: "memory");
    if (warp == 8) {
      if (lane == 0) {
        int s = 1, ph = 0;
        for (int it = G1_STAGES; it < 64; it++) {
          const int ks = it & 15, hp = cg * 4 + (it >> 4);
          const uint32_t st = sb + s * G1_STAGE, fb = bar_full1 + 8 * s;
          mbar_wait(bar_empty1 + 8 * s, ph);
          mbar_expect_tx(fb, G1_STAGE);
          tma_load_2d(st, &tm.x[br], e * 1024 + ks * 64, rb * 128, fb);
          tma_load_3d_mc(st + A_BYTES + e * 12288, &tm.w[br], hp * 64, ks * 64 + e * 32, 0, fb, (uint16_t)3);
          if (it == 8) { prefetch_tmap(&tm.wo[br]); prefetch_tmap(&tm.out); }
          if (++s == G1_STAGES) s = 0;
          if (s == 1) ph ^= 1;
        }
        for (int it = 0; it < 16; it++) {
          const int kb = (it & 3) * 4 + (it >> 2), s2 = it & 3;
          const uint32_t st = sb + s2 * G2_STAGE, fb = bar_full2 + 8 * s2;
          if (it < G2_STAGES) {
            if (it == 0) mbar_wait(bar_empty1, 1);
            mbar_wait(bar_empty1 + 8 * (it + 1), 0);
          } else {
            mbar_wait(bar_empty2 + 8 * s2, ((it >> 2) - 1) & 1);
          }
          mbar_expect_tx(fb, G2_STAGE);
          tma_load_3d_mc(st + A_BYTES + e * 16384, &tm.wo[br], 0, kb * 64 + e * 32, cg * 4, fb, (uint16_t)3);
          if ((it & 3) == 0) mbar_wait(bar_o + 8 * (it >> 2), 0);
          bulk_load(st, g_o + (((br * 8 + rb) * 2 + e) * 16 + kb) * 1024, A_BYTES, fb);
        }
      }
    } else {
      const unsigned tag = __ldcg(&g_epoch[cta]) + 1u;
      if (warp < 11) {
        const int half = warp - 9;
        ulonglong2* dst = g_halo + (cta + 8) * 4 * 256 + half * 128 + lane;
        const ulonglong2* src = g_halo + cta * 4 * 256 + half * 128 + lane;
        if (rb < 7) {
          mbar_wait(bar_empty1 + 32, 0);
          const unsigned long long inv = (unsigned long long)(tag - 1u) << 32;
#pragma unroll 1
          for (int t = 0; t < 4; t++) {
#pragma unroll
            for (int p = 0; p < 4; p++)
              asm volatile("st.relaxed.gpu.global.v2.b64 [%0], {%1, %1};" ::"l"(dst + t * 256 + p * 32), "l"(inv) : "memory");
            __nanosleep(500);
          }
        }
#pragma unroll 1
        for (int t = 0; t < 4; t++) {
          mbar_wait(bar_x + 128 + 8 * half, t & 1);
          if (rb < 7) {
            const unsigned long long hi = (unsigned long long)tag << 32;
#pragma unroll
            for (int i = 0; i < 2; i++) {
              const uint4 v = lds128(sb + OFF_X + 8 * 2048 + half * 1024 + i * 512 + lane * 16);
              asm volatile("st.relaxed.gpu.global.v2.b64 [%0], {%1, %2};" ::"l"(dst + t * 256 + i * 64), "l"(hi | v.x), "l"(hi | v.y) : "memory");
              asm volatile("st.relaxed.gpu.global.v2.b64 [%0], {%1, %2};" ::"l"(dst + t * 256 + i * 64 + 32), "l"(hi | v.z), "l"(hi | v.w) : "memory");
            }
          }
          __syncwarp();
          if (lane == 0) mbar_arrive(bar_o_empty);
          unsigned long long v[8];
          if (rb > 0) {
            uint32_t spins = 0;
            while (true) {
#pragma unroll
              for (int p = 0; p < 4; p++)
                asm volatile("ld.relaxed.gpu.global.v2.b64 {%0, %1}, [%2];" : "=l"(v[2 * p]), "=l"(v[2 * p + 1])
                             : "l"(src + t * 256 + p * 32) : "memory");
              bool ok = true;
#pragma unroll
              for (int p = 0; p < 8; p++) ok &= (unsigned)(v[p] >> 32) == tag;
              if (__all_sync(0xffffffffu, ok)) break;
              if (++spins > SPIN_LIMIT) __trap();
            }
          } else {
#pragma unroll
            for (int p = 0; p < 8; p++) v[p] = 0;
          }
#pragma unroll
          for (int i = 0; i < 2; i++)
            sts128(sb + OFF_X + half * 1024 + i * 512 + lane * 16, (uint32_t)v[4 * i], (uint32_t)v[4 * i + 1], (uint32_t)v[4 * i + 2], (uint32_t)v[4 * i + 3]);
          __syncwarp();
          if (lane == 0) { mbar_arrive(bar_x + 8 * half); }
        }
      } else if (lane == 0) {
        unsigned* flag = &g_o_ready[((br * 8 + rb) * 2 + e) * 4];
        uint4* dst = g_o + (((br * 8 + rb) * 2 + e) * 16 + cg * 4) * 1024;
#pragma unroll 1
        for (int t = 0; t < 4; t++, flag++) {
          mbar_wait(bar_o_full, t & 1);
#pragma unroll 1
          for (int i = 0; i < 8; i++, dst += 128) {
            bulk_store(dst, sb + OFF_X + i * 2048, 2048);
            if (i < 7) __nanosleep(t < 3 ? 80 : 50);
          }
          bulk_commit();
          bulk_wait0_read();
          mbar_arrive(bar_o_empty);
          bulk_wait0();
          asm volatile("red.release.gpu.global.add.u32 [%0], 1;" ::"l"(flag) : "memory");
          wait_flag(flag, tag * 4u);
          asm volatile("fence.proxy.async.global;" ::: "memory");
          mbar_arrive(bar_o + 8 * t);
        }
      }
    }
  }
}

typedef CUresult (*EncodeFn)(CUtensorMap*, CUtensorMapDataType, cuuint32_t, void*, const cuuint64_t*, const cuuint64_t*,
                             const cuuint32_t*, const cuuint32_t*, CUtensorMapInterleave, CUtensorMapSwizzle,
                             CUtensorMapL2promotion, CUtensorMapFloatOOBfill);

bool encode(EncodeFn fn, CUtensorMap* m, const void* ptr, int rank, const cuuint64_t* dims, const cuuint64_t* strides,
            const cuuint32_t* box, CUtensorMapL2promotion promo = CU_TENSOR_MAP_L2_PROMOTION_L2_256B) {
  const cuuint32_t es[3] = {1, 1, 1};
  return fn(m, CU_TENSOR_MAP_DATA_TYPE_BFLOAT16, rank, const_cast<void*>(ptr), dims, strides, box, es,
            CU_TENSOR_MAP_INTERLEAVE_NONE, CU_TENSOR_MAP_SWIZZLE_128B, promo,
            CU_TENSOR_MAP_FLOAT_OOB_FILL_NONE) == CUDA_SUCCESS;
}

}

extern "C" void kernel_launch(void* const* d_in, const int* in_sizes, int n_in, void* d_out, int out_size) {
  (void)in_sizes; (void)n_in; (void)out_size;
  void* fp = nullptr;
  cudaDriverEntryPointQueryResult qr;
  if (cudaGetDriverEntryPoint("cuTensorMapEncodeTiled", &fp, cudaEnableDefault, &qr) != cudaSuccess || !fp) return;
  EncodeFn fn = (EncodeFn)fp;
  TMaps tm;
  tm.zero = 0;
  bool ok = true;
  for (int b = 0; b < 2; b++) {
    tm.xp[b] = d_in[3 * b]; tm.wp[b] = d_in[3 * b + 1];
    {
      const cuuint64_t dims[2] = {2048, 1024}, str[1] = {4096};
      const cuuint32_t box[2] = {64, 128};
      ok &= encode(fn, &tm.x[b], d_in[3 * b + 0], 2, dims, str, box);
      ok &= encode(fn, &tm.x0[b], d_in[3 * b + 0], 2, dims, str, box, CU_TENSOR_MAP_L2_PROMOTION_L2_128B);
    }
    {
      const cuuint64_t dims[3] = {1024, 1024, 3}, str[2] = {6144, 2048};
      const cuuint32_t box[3] = {64, 32, 3};
      ok &= encode(fn, &tm.w[b], d_in[3 * b + 1], 3, dims, str, box);
      ok &= encode(fn, &tm.w0[b], d_in[3 * b + 1], 3, dims, str, box, CU_TENSOR_MAP_L2_PROMOTION_L2_128B);
    }
    {
      const cuuint64_t dims[3] = {64, 1024, 16}, str[2] = {2048, 128};
      const cuuint32_t box[3] = {64, 32, 4};
      ok &= encode(fn, &tm.wo[b], d_in[3 * b + 2], 3, dims, str, box);
    }
  }
  {
    const cuuint64_t dims[2] = {4096, 1024}, str[1] = {8192};
    const cuuint32_t box[2] = {64, 16};
    ok &= encode(fn, &tm.out, d_out, 2, dims, str, box);
  }
  if (!ok) return;
  cudaFuncSetAttribute(fused_kernel, cudaFuncAttributeMaxDynamicSharedMemorySize, SMEM_BYTES);
  fused_kernel<<<NUM_CTAS, NUM_THREADS, SMEM_BYTES>>>(tm);
}
```
